```python
import torch

def _softmax(x, axis=-1):
    return torch.softmax(x, dim=axis)
def _gelu(x):
    return torch.nn.functional.gelu(x, approximate="tanh")
def _silu(x):
    return torch.nn.functional.silu(x)
def _sigmoid(x):
    return torch.sigmoid(x)
def _layernorm(x, axis=-1, eps=1e-5):
    m = x.mean(dim=axis, keepdim=True)
    v = x.var(dim=axis, keepdim=True, unbiased=False)
    return (x - m) / torch.sqrt(v + eps)
def _scatter_add(tgt, idx, src, axis=0):
    return tgt.clone().index_add_(axis, idx, src)
def _segment_sum(src, seg, n):
    out = torch.zeros((n,) + src.shape[1:], dtype=src.dtype)
    return out.index_add_(0, seg, src)
def _pad(x, pw):
    flat = tuple(v for pair in reversed(pw) for v in pair)
    return torch.nn.functional.pad(x, flat)

kernel_name = 'standalone__mha_block_cached__near_ridge'

def setup_inputs():

    _w = (lambda a: (lambda t: t.to(torch.bfloat16) if t.is_floating_point() else t)(torch.as_tensor(a)))
    B, Sq, D = 8, 192, 448
    H, Sk, Dh = 16, 1024, 256
    return {
        "x": _w((lambda *s: torch.randn(*s, dtype=torch.bfloat16) * 0.8)(B, Sq, D)),
        "k_cache": _w((lambda *s: torch.randn(*s, dtype=torch.bfloat16) * 0.8)(B, H, Sk, Dh)),
        "v_cache": _w((lambda *s: torch.randn(*s, dtype=torch.bfloat16) * 0.05)(B, H, Sk, Dh)),
        "wq": _w((lambda *s: torch.randn(*s, dtype=torch.bfloat16) * 0.8)(D, H * Dh) * (D ** -0.5)),
        "wo": _w((lambda *s: torch.randn(*s, dtype=torch.bfloat16) * 0.05)(H * Dh, D) * ((H * Dh) ** -0.5)),
    }

def reference(x, k_cache, v_cache, wq, wo):
    B, Sq, D = x.shape
    H, Dh = 16, 256
    q = (lambda x, *d: x.permute(*d))((x @ wq).reshape(B, Sq, H, Dh), 0, 2, 1, 3)
    scores = torch.einsum("bhqd,bhkd->bhqk", q, k_cache) * (Dh ** -0.5)
    p = _softmax(scores, axis=-1)
    o = torch.einsum("bhqk,bhkd->bhqd", p, v_cache)
    return (lambda x, *d: x.permute(*d))(o, 0, 2, 1, 3).reshape(B, Sq, H * Dh) @ wo
```

```cpp
#include <cuda_runtime.h>
#include <cuda_bf16.h>
#include <cuda.h>
#include <stdint.h>

namespace {

constexpr int B_ = 8, SQ = 192, DM = 448, H_ = 16, SK = 1024, DH = 256;
constexpr int NTHREADS = 384;
constexpr int SLOT_BYTES = 32768;
constexpr int Q_BYTES = 98304;
constexpr int QP_STAGE_BYTES = 28672;
constexpr int QP_X_BYTES = 12288;
constexpr int QP_CHUNKS = 14;
constexpr int N_KV = 32;
constexpr int N_SEQ = 39;
constexpr int SMEM_BAR_OFF = Q_BYTES + 4 * SLOT_BYTES;
constexpr int SMEM_TOTAL = SMEM_BAR_OFF + 256 + 1024;

__device__ __nv_bfloat16 g_part[B_ * H_ * SQ * DM];
__device__ unsigned int g_cnt[B_];
__device__ unsigned int g_done[B_];

__device__ __forceinline__ uint32_t smem_u32(const void* p) { return (uint32_t)__cvta_generic_to_shared(p); }
__device__ __forceinline__ void mbar_init(uint32_t a, int c) { asm volatile("mbarrier.init.shared::cta.b64 [%0], %1;" ::"r"(a), "r"(c)); }
__device__ __forceinline__ void mbar_expect(uint32_t a, int bytes) {
  asm volatile("mbarrier.arrive.expect_tx.shared::cta.b64 _, [%0], %1;" ::"r"(a), "r"(bytes) : "memory");
}
__device__ __forceinline__ void mbar_wait(uint32_t a, int parity) {
  asm volatile(
      "{\n.reg .pred p;\n"
      "LAB_WAIT:\n"
      "mbarrier.try_wait.parity.shared::cta.b64 p, [%0], %1;\n"
      "@p bra LAB_DONE;\n"
      "bra LAB_WAIT;\n"
      "LAB_DONE:\n}\n" ::"r"(a), "r"(parity) : "memory");
}
__device__ __forceinline__ void tma2(uint32_t dst, const CUtensorMap* m, int c0, int c1, uint32_t mbar) {
  asm volatile("cp.async.bulk.tensor.2d.shared::cluster.global.mbarrier::complete_tx::bytes [%0], [%1, {%3,%4}], [%2];"
               ::"r"(dst), "l"(m), "r"(mbar), "r"(c0), "r"(c1) : "memory");
}
__device__ __forceinline__ void tma3(uint32_t dst, const CUtensorMap* m, int c0, int c1, int c2, uint32_t mbar) {
  asm volatile("cp.async.bulk.tensor.3d.shared::cluster.global.mbarrier::complete_tx::bytes [%0], [%1, {%3,%4,%5}], [%2];"
               ::"r"(dst), "l"(m), "r"(mbar), "r"(c0), "r"(c1), "r"(c2) : "memory");
}
__device__ __forceinline__ uint32_t atom_inc_smem(uint32_t a) {
  uint32_t old;
  asm volatile("atom.acq_rel.cta.shared::cta.add.u32 %0, [%1], 1;" : "=r"(old) : "r"(a) : "memory");
  return old;
}
__device__ __forceinline__ void wg_fence() { asm volatile("wgmma.fence.sync.aligned;" ::: "memory"); }
__device__ __forceinline__ void wg_commit() { asm volatile("wgmma.commit_group.sync.aligned;" ::: "memory"); }
template <int N> __device__ __forceinline__ void wg_wait() { asm volatile("wgmma.wait_group.sync.aligned %0;" ::"n"(N) : "memory"); }
__device__ __forceinline__ void fence_async_smem() { asm volatile("fence.proxy.async.shared::cta;" ::: "memory"); }
__device__ __forceinline__ void bar_sync(int id, int n) { asm volatile("bar.sync %0, %1;" ::"r"(id), "r"(n) : "memory"); }
template <int N> __device__ __forceinline__ void fence_regs(float (&d)[N]) {
#pragma unroll
  for (int i = 0; i < N; i++) asm volatile("" : "+f"(d[i])::"memory");
}
__device__ __forceinline__ uint32_t pack_bf16(float lo, float hi) {
  uint32_t r;
  asm("cvt.rn.bf16x2.f32 %0, %1, %2;" : "=r"(r) : "f"(hi), "f"(lo));
  return r;
}
__device__ __forceinline__ float ex2(float x) {
  float y;
  asm("ex2.approx.ftz.f32 %0, %1;" : "=f"(y) : "f"(x));
  return y;
}
__device__ __forceinline__ void stsm4(uint32_t addr, uint32_t r0, uint32_t r1, uint32_t r2, uint32_t r3) {
  asm volatile("stmatrix.sync.aligned.m8n8.x4.shared.b16 [%0], {%1,%2,%3,%4};" ::"r"(addr), "r"(r0), "r"(r1), "r"(r2), "r"(r3) : "memory");
}
__device__ __forceinline__ uint64_t make_desc(uint32_t addr, uint32_t lbo, uint32_t sbo, uint32_t swz) {
  return (uint64_t)((addr & 0x3FFFF) >> 4) | ((uint64_t)(lbo >> 4) << 16) | ((uint64_t)(sbo >> 4) << 32) | ((uint64_t)swz << 62);
}

__device__ __forceinline__ void wgmma_n256_ss_tb(float (&d)[128], uint64_t da, uint64_t db, int scale_d) {
  asm volatile("{\n.reg .pred p;\nsetp.ne.b32 p, %130, 0;\n"
    "wgmma.mma_async.sync.aligned.m64n256k16.f32.bf16.bf16 {%0, %1, %2, %3, %4, %5, %6, %7, %8, %9, %10, %11, %12, %13, %14, %15, %16, %17, %18, %19, %20, %21, %22, %23, %24, %25, %26, %27, %28, %29, %30, %31, %32, %33, %34, %35, %36, %37, %38, %39, %40, %41, %42, %43, %44, %45, %46, %47, %48, %49, %50, %51, %52, %53, %54, %55, %56, %57, %58, %59, %60, %61, %62, %63, %64, %65, %66, %67, %68, %69, %70, %71, %72, %73, %74, %75, %76, %77, %78, %79, %80, %81, %82, %83, %84, %85, %86, %87, %88, %89, %90, %91, %92, %93, %94, %95, %96, %97, %98, %99, %100, %101, %102, %103, %104, %105, %106, %107, %108, %109, %110, %111, %112, %113, %114, %115, %116, %117, %118, %119, %120, %121, %122, %123, %124, %125, %126, %127}, %128, %129, p, 1, 1, 0, 1;\n}\n"
    : "+f"(d[0]), "+f"(d[1]), "+f"(d[2]), "+f"(d[3]), "+f"(d[4]), "+f"(d[5]), "+f"(d[6]), "+f"(d[7]), "+f"(d[8]), "+f"(d[9]), "+f"(d[10]), "+f"(d[11]), "+f"(d[12]), "+f"(d[13]), "+f"(d[14]), "+f"(d[15]), "+f"(d[16]), "+f"(d[17]), "+f"(d[18]), "+f"(d[19]), "+f"(d[20]), "+f"(d[21]), "+f"(d[22]), "+f"(d[23]), "+f"(d[24]), "+f"(d[25]), "+f"(d[26]), "+f"(d[27]), "+f"(d[28]), "+f"(d[29]), "+f"(d[30]), "+f"(d[31]), "+f"(d[32]), "+f"(d[33]), "+f"(d[34]), "+f"(d[35]), "+f"(d[36]), "+f"(d[37]), "+f"(d[38]), "+f"(d[39]), "+f"(d[40]), "+f"(d[41]), "+f"(d[42]), "+f"(d[43]), "+f"(d[44]), "+f"(d[45]), "+f"(d[46]), "+f"(d[47]), "+f"(d[48]), "+f"(d[49]), "+f"(d[50]), "+f"(d[51]), "+f"(d[52]), "+f"(d[53]), "+f"(d[54]), "+f"(d[55]), "+f"(d[56]), "+f"(d[57]), "+f"(d[58]), "+f"(d[59]), "+f"(d[60]), "+f"(d[61]), "+f"(d[62]), "+f"(d[63]), "+f"(d[64]), "+f"(d[65]), "+f"(d[66]), "+f"(d[67]), "+f"(d[68]), "+f"(d[69]), "+f"(d[70]), "+f"(d[71]), "+f"(d[72]), "+f"(d[73]), "+f"(d[74]), "+f"(d[75]), "+f"(d[76]), "+f"(d[77]), "+f"(d[78]), "+f"(d[79]), "+f"(d[80]), "+f"(d[81]), "+f"(d[82]), "+f"(d[83]), "+f"(d[84]), "+f"(d[85]), "+f"(d[86]), "+f"(d[87]), "+f"(d[88]), "+f"(d[89]), "+f"(d[90]), "+f"(d[91]), "+f"(d[92]), "+f"(d[93]), "+f"(d[94]), "+f"(d[95]), "+f"(d[96]), "+f"(d[97]), "+f"(d[98]), "+f"(d[99]), "+f"(d[100]), "+f"(d[101]), "+f"(d[102]), "+f"(d[103]), "+f"(d[104]), "+f"(d[105]), "+f"(d[106]), "+f"(d[107]), "+f"(d[108]), "+f"(d[109]), "+f"(d[110]), "+f"(d[111]), "+f"(d[112]), "+f"(d[113]), "+f"(d[114]), "+f"(d[115]), "+f"(d[116]), "+f"(d[117]), "+f"(d[118]), "+f"(d[119]), "+f"(d[120]), "+f"(d[121]), "+f"(d[122]), "+f"(d[123]), "+f"(d[124]), "+f"(d[125]), "+f"(d[126]), "+f"(d[127])
    : "l"(da), "l"(db), "r"(scale_d));
}
__device__ __forceinline__ void wgmma_n64_ss(float (&d)[32], uint64_t da, uint64_t db, int scale_d) {
  asm volatile("{\n.reg .pred p;\nsetp.ne.b32 p, %34, 0;\n"
    "wgmma.mma_async.sync.aligned.m64n64k16.f32.bf16.bf16 {%0, %1, %2, %3, %4, %5, %6, %7, %8, %9, %10, %11, %12, %13, %14, %15, %16, %17, %18, %19, %20, %21, %22, %23, %24, %25, %26, %27, %28, %29, %30, %31}, %32, %33, p, 1, 1, 0, 0;\n}\n"
    : "+f"(d[0]), "+f"(d[1]), "+f"(d[2]), "+f"(d[3]), "+f"(d[4]), "+f"(d[5]), "+f"(d[6]), "+f"(d[7]), "+f"(d[8]), "+f"(d[9]), "+f"(d[10]), "+f"(d[11]), "+f"(d[12]), "+f"(d[13]), "+f"(d[14]), "+f"(d[15]), "+f"(d[16]), "+f"(d[17]), "+f"(d[18]), "+f"(d[19]), "+f"(d[20]), "+f"(d[21]), "+f"(d[22]), "+f"(d[23]), "+f"(d[24]), "+f"(d[25]), "+f"(d[26]), "+f"(d[27]), "+f"(d[28]), "+f"(d[29]), "+f"(d[30]), "+f"(d[31])
    : "l"(da), "l"(db), "r"(scale_d));
}
__device__ __forceinline__ void wgmma_n256_rs_tb(float (&d)[128], uint32_t a0, uint32_t a1, uint32_t a2, uint32_t a3, uint64_t db, int scale_d) {
  asm volatile("{\n.reg .pred p;\nsetp.ne.b32 p, %133, 0;\n"
    "wgmma.mma_async.sync.aligned.m64n256k16.f32.bf16.bf16 {%0, %1, %2, %3, %4, %5, %6, %7, %8, %9, %10, %11, %12, %13, %14, %15, %16, %17, %18, %19, %20, %21, %22, %23, %24, %25, %26, %27, %28, %29, %30, %31, %32, %33, %34, %35, %36, %37, %38, %39, %40, %41, %42, %43, %44, %45, %46, %47, %48, %49, %50, %51, %52, %53, %54, %55, %56, %57, %58, %59, %60, %61, %62, %63, %64, %65, %66, %67, %68, %69, %70, %71, %72, %73, %74, %75, %76, %77, %78, %79, %80, %81, %82, %83, %84, %85, %86, %87, %88, %89, %90, %91, %92, %93, %94, %95, %96, %97, %98, %99, %100, %101, %102, %103, %104, %105, %106, %107, %108, %109, %110, %111, %112, %113, %114, %115, %116, %117, %118, %119, %120, %121, %122, %123, %124, %125, %126, %127}, {%128, %129, %130, %131}, %132, p, 1, 1, 1;\n}\n"
    : "+f"(d[0]), "+f"(d[1]), "+f"(d[2]), "+f"(d[3]), "+f"(d[4]), "+f"(d[5]), "+f"(d[6]), "+f"(d[7]), "+f"(d[8]), "+f"(d[9]), "+f"(d[10]), "+f"(d[11]), "+f"(d[12]), "+f"(d[13]), "+f"(d[14]), "+f"(d[15]), "+f"(d[16]), "+f"(d[17]), "+f"(d[18]), "+f"(d[19]), "+f"(d[20]), "+f"(d[21]), "+f"(d[22]), "+f"(d[23]), "+f"(d[24]), "+f"(d[25]), "+f"(d[26]), "+f"(d[27]), "+f"(d[28]), "+f"(d[29]), "+f"(d[30]), "+f"(d[31]), "+f"(d[32]), "+f"(d[33]), "+f"(d[34]), "+f"(d[35]), "+f"(d[36]), "+f"(d[37]), "+f"(d[38]), "+f"(d[39]), "+f"(d[40]), "+f"(d[41]), "+f"(d[42]), "+f"(d[43]), "+f"(d[44]), "+f"(d[45]), "+f"(d[46]), "+f"(d[47]), "+f"(d[48]), "+f"(d[49]), "+f"(d[50]), "+f"(d[51]), "+f"(d[52]), "+f"(d[53]), "+f"(d[54]), "+f"(d[55]), "+f"(d[56]), "+f"(d[57]), "+f"(d[58]), "+f"(d[59]), "+f"(d[60]), "+f"(d[61]), "+f"(d[62]), "+f"(d[63]), "+f"(d[64]), "+f"(d[65]), "+f"(d[66]), "+f"(d[67]), "+f"(d[68]), "+f"(d[69]), "+f"(d[70]), "+f"(d[71]), "+f"(d[72]), "+f"(d[73]), "+f"(d[74]), "+f"(d[75]), "+f"(d[76]), "+f"(d[77]), "+f"(d[78]), "+f"(d[79]), "+f"(d[80]), "+f"(d[81]), "+f"(d[82]), "+f"(d[83]), "+f"(d[84]), "+f"(d[85]), "+f"(d[86]), "+f"(d[87]), "+f"(d[88]), "+f"(d[89]), "+f"(d[90]), "+f"(d[91]), "+f"(d[92]), "+f"(d[93]), "+f"(d[94]), "+f"(d[95]), "+f"(d[96]), "+f"(d[97]), "+f"(d[98]), "+f"(d[99]), "+f"(d[100]), "+f"(d[101]), "+f"(d[102]), "+f"(d[103]), "+f"(d[104]), "+f"(d[105]), "+f"(d[106]), "+f"(d[107]), "+f"(d[108]), "+f"(d[109]), "+f"(d[110]), "+f"(d[111]), "+f"(d[112]), "+f"(d[113]), "+f"(d[114]), "+f"(d[115]), "+f"(d[116]), "+f"(d[117]), "+f"(d[118]), "+f"(d[119]), "+f"(d[120]), "+f"(d[121]), "+f"(d[122]), "+f"(d[123]), "+f"(d[124]), "+f"(d[125]), "+f"(d[126]), "+f"(d[127])
    : "r"(a0), "r"(a1), "r"(a2), "r"(a3), "l"(db), "r"(scale_d));
}
__device__ __forceinline__ void wgmma_n64_rs_tb(float (&d)[32], uint32_t a0, uint32_t a1, uint32_t a2, uint32_t a3, uint64_t db, int scale_d) {
  asm volatile("{\n.reg .pred p;\nsetp.ne.b32 p, %37, 0;\n"
    "wgmma.mma_async.sync.aligned.m64n64k16.f32.bf16.bf16 {%0, %1, %2, %3, %4, %5, %6, %7, %8, %9, %10, %11, %12, %13, %14, %15, %16, %17, %18, %19, %20, %21, %22, %23, %24, %25, %26, %27, %28, %29, %30, %31}, {%32, %33, %34, %35}, %36, p, 1, 1, 1;\n}\n"
    : "+f"(d[0]), "+f"(d[1]), "+f"(d[2]), "+f"(d[3]), "+f"(d[4]), "+f"(d[5]), "+f"(d[6]), "+f"(d[7]), "+f"(d[8]), "+f"(d[9]), "+f"(d[10]), "+f"(d[11]), "+f"(d[12]), "+f"(d[13]), "+f"(d[14]), "+f"(d[15]), "+f"(d[16]), "+f"(d[17]), "+f"(d[18]), "+f"(d[19]), "+f"(d[20]), "+f"(d[21]), "+f"(d[22]), "+f"(d[23]), "+f"(d[24]), "+f"(d[25]), "+f"(d[26]), "+f"(d[27]), "+f"(d[28]), "+f"(d[29]), "+f"(d[30]), "+f"(d[31])
    : "r"(a0), "r"(a1), "r"(a2), "r"(a3), "l"(db), "r"(scale_d));
}
__device__ __forceinline__ void wgmma_n64_ss_tb(float (&d)[32], uint64_t da, uint64_t db, int scale_d) {
  asm volatile("{\n.reg .pred p;\nsetp.ne.b32 p, %34, 0;\n"
    "wgmma.mma_async.sync.aligned.m64n64k16.f32.bf16.bf16 {%0, %1, %2, %3, %4, %5, %6, %7, %8, %9, %10, %11, %12, %13, %14, %15, %16, %17, %18, %19, %20, %21, %22, %23, %24, %25, %26, %27, %28, %29, %30, %31}, %32, %33, p, 1, 1, 0, 1;\n}\n"
    : "+f"(d[0]), "+f"(d[1]), "+f"(d[2]), "+f"(d[3]), "+f"(d[4]), "+f"(d[5]), "+f"(d[6]), "+f"(d[7]), "+f"(d[8]), "+f"(d[9]), "+f"(d[10]), "+f"(d[11]), "+f"(d[12]), "+f"(d[13]), "+f"(d[14]), "+f"(d[15]), "+f"(d[16]), "+f"(d[17]), "+f"(d[18]), "+f"(d[19]), "+f"(d[20]), "+f"(d[21]), "+f"(d[22]), "+f"(d[23]), "+f"(d[24]), "+f"(d[25]), "+f"(d[26]), "+f"(d[27]), "+f"(d[28]), "+f"(d[29]), "+f"(d[30]), "+f"(d[31])
    : "l"(da), "l"(db), "r"(scale_d));
}
__device__ __forceinline__ void wgmma_n128_rs_tb(float (&d)[64], uint32_t a0, uint32_t a1, uint32_t a2, uint32_t a3, uint64_t db, int scale_d) {
  asm volatile("{\n.reg .pred p;\nsetp.ne.b32 p, %69, 0;\n"
    "wgmma.mma_async.sync.aligned.m64n128k16.f32.bf16.bf16 {%0, %1, %2, %3, %4, %5, %6, %7, %8, %9, %10, %11, %12, %13, %14, %15, %16, %17, %18, %19, %20, %21, %22, %23, %24, %25, %26, %27, %28, %29, %30, %31, %32, %33, %34, %35, %36, %37, %38, %39, %40, %41, %42, %43, %44, %45, %46, %47, %48, %49, %50, %51, %52, %53, %54, %55, %56, %57, %58, %59, %60, %61, %62, %63}, {%64, %65, %66, %67}, %68, p, 1, 1, 1;\n}\n"
    : "+f"(d[0]), "+f"(d[1]), "+f"(d[2]), "+f"(d[3]), "+f"(d[4]), "+f"(d[5]), "+f"(d[6]), "+f"(d[7]), "+f"(d[8]), "+f"(d[9]), "+f"(d[10]), "+f"(d[11]), "+f"(d[12]), "+f"(d[13]), "+f"(d[14]), "+f"(d[15]), "+f"(d[16]), "+f"(d[17]), "+f"(d[18]), "+f"(d[19]), "+f"(d[20]), "+f"(d[21]), "+f"(d[22]), "+f"(d[23]), "+f"(d[24]), "+f"(d[25]), "+f"(d[26]), "+f"(d[27]), "+f"(d[28]), "+f"(d[29]), "+f"(d[30]), "+f"(d[31]), "+f"(d[32]), "+f"(d[33]), "+f"(d[34]), "+f"(d[35]), "+f"(d[36]), "+f"(d[37]), "+f"(d[38]), "+f"(d[39]), "+f"(d[40]), "+f"(d[41]), "+f"(d[42]), "+f"(d[43]), "+f"(d[44]), "+f"(d[45]), "+f"(d[46]), "+f"(d[47]), "+f"(d[48]), "+f"(d[49]), "+f"(d[50]), "+f"(d[51]), "+f"(d[52]), "+f"(d[53]), "+f"(d[54]), "+f"(d[55]), "+f"(d[56]), "+f"(d[57]), "+f"(d[58]), "+f"(d[59]), "+f"(d[60]), "+f"(d[61]), "+f"(d[62]), "+f"(d[63])
    : "r"(a0), "r"(a1), "r"(a2), "r"(a3), "l"(db), "r"(scale_d));
}
__device__ __forceinline__ void wgmma_n128_ss_tb(float (&d)[64], uint64_t da, uint64_t db, int scale_d) {
  asm volatile("{\n.reg .pred p;\nsetp.ne.b32 p, %66, 0;\n"
    "wgmma.mma_async.sync.aligned.m64n128k16.f32.bf16.bf16 {%0, %1, %2, %3, %4, %5, %6, %7, %8, %9, %10, %11, %12, %13, %14, %15, %16, %17, %18, %19, %20, %21, %22, %23, %24, %25, %26, %27, %28, %29, %30, %31, %32, %33, %34, %35, %36, %37, %38, %39, %40, %41, %42, %43, %44, %45, %46, %47, %48, %49, %50, %51, %52, %53, %54, %55, %56, %57, %58, %59, %60, %61, %62, %63}, %64, %65, p, 1, 1, 0, 1;\n}\n"
    : "+f"(d[0]), "+f"(d[1]), "+f"(d[2]), "+f"(d[3]), "+f"(d[4]), "+f"(d[5]), "+f"(d[6]), "+f"(d[7]), "+f"(d[8]), "+f"(d[9]), "+f"(d[10]), "+f"(d[11]), "+f"(d[12]), "+f"(d[13]), "+f"(d[14]), "+f"(d[15]), "+f"(d[16]), "+f"(d[17]), "+f"(d[18]), "+f"(d[19]), "+f"(d[20]), "+f"(d[21]), "+f"(d[22]), "+f"(d[23]), "+f"(d[24]), "+f"(d[25]), "+f"(d[26]), "+f"(d[27]), "+f"(d[28]), "+f"(d[29]), "+f"(d[30]), "+f"(d[31]), "+f"(d[32]), "+f"(d[33]), "+f"(d[34]), "+f"(d[35]), "+f"(d[36]), "+f"(d[37]), "+f"(d[38]), "+f"(d[39]), "+f"(d[40]), "+f"(d[41]), "+f"(d[42]), "+f"(d[43]), "+f"(d[44]), "+f"(d[45]), "+f"(d[46]), "+f"(d[47]), "+f"(d[48]), "+f"(d[49]), "+f"(d[50]), "+f"(d[51]), "+f"(d[52]), "+f"(d[53]), "+f"(d[54]), "+f"(d[55]), "+f"(d[56]), "+f"(d[57]), "+f"(d[58]), "+f"(d[59]), "+f"(d[60]), "+f"(d[61]), "+f"(d[62]), "+f"(d[63])
    : "l"(da), "l"(db), "r"(scale_d));
}

#define STAMP(i)

struct Params {
  CUtensorMap x, wq, k, v, wo;
};

__device__ __forceinline__ void issue_seq(const Params& P, int n, uint32_t sbase, int bh, int h) {
  const uint32_t slot = n & 3;
  const uint32_t bar = sbase + SMEM_BAR_OFF + slot * 8;
  const uint32_t dst = sbase + Q_BYTES + slot * SLOT_BYTES;
  mbar_expect(bar, SLOT_BYTES);
  if (n < N_KV) {
    tma3(dst, (n & 1) ? &P.v : &P.k, 0, bh * SK + (n >> 1) * 64, 0, bar);
  } else {
    tma2(dst, &P.wo, (n - N_KV) * 64, h * DH, bar);
  }
}
__device__ __forceinline__ void issue_qp(const Params& P, int c, uint32_t sbase, int b, int h) {
  const uint32_t st = c % 3;
  const uint32_t bar = sbase + SMEM_BAR_OFF + 32 + st * 8;
  const uint32_t dst = sbase + st * QP_STAGE_BYTES;
  mbar_expect(bar, QP_STAGE_BYTES);
  tma2(dst, &P.x, c * 32, b * SQ, bar);
  tma3(dst + QP_X_BYTES, &P.wq, 0, c * 32, h * 4, bar);
}

__global__ void __launch_bounds__(NTHREADS, 1)
mha_fused_kernel(const __grid_constant__ Params P, __nv_bfloat16* __restrict__ out) {
  extern __shared__ char smem_raw[];
  const uint32_t sbase = (smem_u32(smem_raw) + 1023u) & ~1023u;
  const int tid = threadIdx.x;
  const int lane = tid & 31;
  const int warp = tid >> 5;
  const int wg = tid >> 7;
  const int bh = blockIdx.x;
  const int b = bh >> 4, h = bh & 15;
  const uint32_t bar_full = sbase + SMEM_BAR_OFF;
  const uint32_t bar_qp = sbase + SMEM_BAR_OFF + 32;
  const uint32_t cnt_kv = sbase + SMEM_BAR_OFF + 64;
  const uint32_t cnt_qp = sbase + SMEM_BAR_OFF + 80;

  STAMP(0);
  if (tid == 0) {
    for (int i = 0; i < 4; i++) mbar_init(bar_full + i * 8, 1);
    for (int i = 0; i < 3; i++) mbar_init(bar_qp + i * 8, 1);
    for (int i = 0; i < 7; i++) asm volatile("st.shared.u32 [%0], %1;" ::"r"(cnt_kv + i * 4), "r"(0) : "memory");
    asm volatile("fence.mbarrier_init.release.cluster;" ::: "memory");
    fence_async_smem();
    for (int c = 0; c < 3; c++) issue_qp(P, c, sbase, b, h);
    for (int n = 0; n < 4; n++) issue_seq(P, n, sbase, bh, h);
  }
  __syncthreads();

  float o[128];
  {
#pragma unroll 1
    for (int c = 0; c < QP_CHUNKS; c++) {
      const int st = c % 3;
      const int use = c / 3;
      mbar_wait(bar_qp + st * 8, use & 1);
      const uint32_t xa = sbase + st * QP_STAGE_BYTES + wg * 4096;
      const uint32_t wa = sbase + st * QP_STAGE_BYTES + QP_X_BYTES;
      wg_fence();
      wgmma_n256_ss_tb(o, make_desc(xa, 16, 512, 2), make_desc(wa, 4096, 1024, 1), c > 0);
      wgmma_n256_ss_tb(o, make_desc(xa + 32, 16, 512, 2), make_desc(wa + 2048, 4096, 1024, 1), 1);
      wg_commit();
      wg_wait<0>();
      fence_regs(o);
      if (lane == 0) {
        uint32_t old = atom_inc_smem(cnt_qp + st * 4);
        if (old == 12u * use + 11u && c + 3 < QP_CHUNKS) issue_qp(P, c + 3, sbase, b, h);
      }
      __syncwarp();
    }
    __syncthreads();
    const int r = (warp & 3) * 16 + (lane & 7) + ((lane >> 3) & 1) * 8;
    const uint32_t qrow = sbase + wg * 32768 + r * 128;
#pragma unroll
    for (int j = 0; j < 32; j += 2) {
      const int cg = j + (lane >> 4);
      const uint32_t addr = qrow + (cg >> 3) * 8192 + (((cg & 7) ^ (r & 7)) << 4);
      stsm4(addr, pack_bf16(o[4 * j], o[4 * j + 1]), pack_bf16(o[4 * j + 2], o[4 * j + 3]),
            pack_bf16(o[4 * j + 4], o[4 * j + 5]), pack_bf16(o[4 * j + 6], o[4 * j + 7]));
    }
    fence_async_smem();
    bar_sync(1 + wg, 128);
  }
  STAMP(1);

  const float cs = 0.0625f * 1.4426950408889634f;
  float ms0 = -INFINITY, ms1 = -INFINITY, l0 = 0.f, l1 = 0.f;
#pragma unroll
  for (int i = 0; i < 128; i++) o[i] = 0.f;
  const uint32_t qa = sbase + wg * 32768;
#pragma unroll 1
  for (int j = 0; j < 16; j++) {
    const int sk = (j & 1) * 2;
    const int par = (j >> 1) & 1;
    const uint32_t ka = sbase + Q_BYTES + sk * SLOT_BYTES;
    const uint32_t va = ka + SLOT_BYTES;
    float s[32];
    mbar_wait(bar_full + sk * 8, par);
    wg_fence();
#pragma unroll
    for (int kk = 0; kk < 16; kk++) {
      const uint32_t off = (kk >> 2) * 8192 + (kk & 3) * 32;
      wgmma_n64_ss(s, make_desc(qa + off, 16, 1024, 1), make_desc(ka + off, 16, 1024, 1), kk > 0);
    }
    wg_commit();
    wg_wait<0>();
    fence_regs(s);
    if (lane == 0) {
      uint32_t old = atom_inc_smem(cnt_kv + sk * 4);
      if (old == 12u * (j >> 1) + 11u) issue_seq(P, 2 * j + 4, sbase, bh, h);
    }
    __syncwarp();
    float mx0 = fmaxf(s[0], s[1]), mx1 = fmaxf(s[2], s[3]);
#pragma unroll
    for (int i = 1; i < 8; i++) {
      mx0 = fmaxf(mx0, fmaxf(s[4 * i], s[4 * i + 1]));
      mx1 = fmaxf(mx1, fmaxf(s[4 * i + 2], s[4 * i + 3]));
    }
    mx0 = fmaxf(mx0, __shfl_xor_sync(0xffffffffu, mx0, 1));
    mx1 = fmaxf(mx1, __shfl_xor_sync(0xffffffffu, mx1, 1));
    mx0 = fmaxf(mx0, __shfl_xor_sync(0xffffffffu, mx0, 2));
    mx1 = fmaxf(mx1, __shfl_xor_sync(0xffffffffu, mx1, 2));
    const float mn0 = fmaxf(ms0, mx0 * cs), mn1 = fmaxf(ms1, mx1 * cs);
    if (__any_sync(0xffffffffu, (mn0 > ms0) || (mn1 > ms1))) {
      const float a0 = ex2(ms0 - mn0), a1 = ex2(ms1 - mn1);
      l0 *= a0; l1 *= a1;
#pragma unroll
      for (int i = 0; i < 32; i++) {
        o[4 * i] *= a0; o[4 * i + 1] *= a0; o[4 * i + 2] *= a1; o[4 * i + 3] *= a1;
      }
      ms0 = mn0; ms1 = mn1;
    }
    uint32_t p[16];
#pragma unroll
    for (int i = 0; i < 8; i++) {
      const float e0 = ex2(fmaf(s[4 * i], cs, -ms0)), e1 = ex2(fmaf(s[4 * i + 1], cs, -ms0));
      const float e2 = ex2(fmaf(s[4 * i + 2], cs, -ms1)), e3 = ex2(fmaf(s[4 * i + 3], cs, -ms1));
      l0 += e0 + e1; l1 += e2 + e3;
      p[2 * i] = pack_bf16(e0, e1);
      p[2 * i + 1] = pack_bf16(e2, e3);
    }
    mbar_wait(bar_full + sk * 8 + 8, par);
    wg_fence();
#pragma unroll
    for (int kk = 0; kk < 4; kk++) {
      wgmma_n256_rs_tb(o, p[4 * kk], p[4 * kk + 1], p[4 * kk + 2], p[4 * kk + 3], make_desc(va + kk * 2048, 8192, 1024, 1), 1);
    }
    wg_commit();
    wg_wait<0>();
    fence_regs(o);
    if (lane == 0) {
      uint32_t old = atom_inc_smem(cnt_kv + sk * 4 + 4);
      if (old == 12u * (j >> 1) + 11u) issue_seq(P, 2 * j + 5, sbase, bh, h);
    }
    __syncwarp();
  }
  STAMP(2);

  l0 += __shfl_xor_sync(0xffffffffu, l0, 1); l1 += __shfl_xor_sync(0xffffffffu, l1, 1);
  l0 += __shfl_xor_sync(0xffffffffu, l0, 2); l1 += __shfl_xor_sync(0xffffffffu, l1, 2);
  const float il0 = 1.0f / l0, il1 = 1.0f / l1;
  uint32_t oa[64];
#pragma unroll
  for (int i = 0; i < 32; i++) {
    oa[2 * i] = pack_bf16(o[4 * i] * il0, o[4 * i + 1] * il0);
    oa[2 * i + 1] = pack_bf16(o[4 * i + 2] * il1, o[4 * i + 3] * il1);
  }
  __nv_bfloat16* prow = g_part + (size_t)bh * SQ * DM + (size_t)(wg * 64 + (warp & 3) * 16 + (lane >> 2)) * DM + (lane & 3) * 2;
#pragma unroll 1
  for (int t = 0; t < 7; t++) {
    const int n = N_KV + t;
    const int sl = n & 3;
    const uint32_t wa = sbase + Q_BYTES + sl * SLOT_BYTES;
    float acc[32];
    mbar_wait(bar_full + sl * 8, (n >> 2) & 1);
    wg_fence();
#pragma unroll
    for (int kk = 0; kk < 16; kk++) {
      wgmma_n64_rs_tb(acc, oa[4 * kk], oa[4 * kk + 1], oa[4 * kk + 2], oa[4 * kk + 3], make_desc(wa + kk * 2048, 8192, 1024, 1), kk > 0);
    }
    wg_commit();
    wg_wait<0>();
    fence_regs(acc);
    if (lane == 0) {
      uint32_t old = atom_inc_smem(cnt_kv + sl * 4);
      if (old == 12u * (n >> 2) + 11u && n + 4 < N_SEQ) issue_seq(P, n + 4, sbase, bh, h);
    }
    __syncwarp();
#pragma unroll
    for (int i = 0; i < 8; i++) {
      *(uint32_t*)(prow + t * 64 + i * 8) = pack_bf16(acc[4 * i], acc[4 * i + 1]);
      *(uint32_t*)(prow + 8 * DM + t * 64 + i * 8) = pack_bf16(acc[4 * i + 2], acc[4 * i + 3]);
    }
  }
  STAMP(3);
  __threadfence();
  __syncthreads();
  if (tid == 0) {
    atomicAdd(&g_cnt[b], 1u);
    unsigned int v;
    int guard = 0;
    do {
      asm volatile("ld.acquire.gpu.global.u32 %0, [%1];" : "=r"(v) : "l"(&g_cnt[b]) : "memory");
    } while (v < 16u && ++guard < (1 << 24));
  }
  __syncthreads();
  STAMP(4);
  for (int idx = tid; idx < 12 * 56; idx += NTHREADS) {
    const int row = h * 12 + idx / 56, c16 = idx % 56;
    float a[8];
#pragma unroll
    for (int i = 0; i < 8; i++) a[i] = 0.f;
    const uint4* src = (const uint4*)(g_part + (size_t)b * H_ * SQ * DM + (size_t)row * DM) + c16;
#pragma unroll
    for (int hh = 0; hh < 16; hh++) {
      const uint4 v = __ldcg(src + (size_t)hh * (SQ * DM / 8));
      const uint32_t w[4] = {v.x, v.y, v.z, v.w};
#pragma unroll
      for (int i = 0; i < 4; i++) {
        a[2 * i] += __uint_as_float(w[i] << 16);
        a[2 * i + 1] += __uint_as_float(w[i] & 0xffff0000u);
      }
    }
    uint4 r;
    r.x = pack_bf16(a[0], a[1]); r.y = pack_bf16(a[2], a[3]); r.z = pack_bf16(a[4], a[5]); r.w = pack_bf16(a[6], a[7]);
    *((uint4*)(out + ((size_t)b * SQ + row) * DM) + c16) = r;
  }
  __syncthreads();
  if (tid == 0) {
    unsigned int d = atomicAdd(&g_done[b], 1u);
    if (d == 15u) { g_cnt[b] = 0u; g_done[b] = 0u; __threadfence(); }
  }
  STAMP(5);
}

typedef CUresult (*EncFn)(CUtensorMap*, CUtensorMapDataType, cuuint32_t, void*, const cuuint64_t*, const cuuint64_t*,
                          const cuuint32_t*, const cuuint32_t*, CUtensorMapInterleave, CUtensorMapSwizzle,
                          CUtensorMapL2promotion, CUtensorMapFloatOOBfill);

}

extern "C" void kernel_launch(void* const* d_in, const int* in_sizes, int n_in, void* d_out, int out_size) {
  static EncFn enc = nullptr;
  static Params P;
  static const void* cached[5] = {nullptr, nullptr, nullptr, nullptr, nullptr};
  if (!enc) {
    cudaDriverEntryPointQueryResult qr;
    cudaGetDriverEntryPoint("cuTensorMapEncodeTiled", (void**)&enc, cudaEnableDefault, &qr);
    cudaFuncSetAttribute(mha_fused_kernel, cudaFuncAttributeMaxDynamicSharedMemorySize, SMEM_TOTAL);
  }
  bool same = true;
  for (int i = 0; i < 5; i++) same = same && (cached[i] == d_in[i]);
  if (!same) {
    const cuuint32_t es[3] = {1, 1, 1};
    {
      cuuint64_t dims[2] = {DM, B_ * SQ}; cuuint64_t str[1] = {DM * 2}; cuuint32_t box[2] = {32, SQ};
      enc(&P.x, CU_TENSOR_MAP_DATA_TYPE_BFLOAT16, 2, d_in[0], dims, str, box, es, CU_TENSOR_MAP_INTERLEAVE_NONE,
          CU_TENSOR_MAP_SWIZZLE_64B, CU_TENSOR_MAP_L2_PROMOTION_L2_128B, CU_TENSOR_MAP_FLOAT_OOB_FILL_NONE);
    }
    for (int w = 0; w < 2; w++) {
      cuuint64_t dims[3] = {64, (cuuint64_t)B_ * H_ * SK, 4}; cuuint64_t str[2] = {DH * 2, 128}; cuuint32_t box[3] = {64, 64, 4};
      enc(w ? &P.v : &P.k, CU_TENSOR_MAP_DATA_TYPE_BFLOAT16, 3, d_in[1 + w], dims, str, box, es, CU_TENSOR_MAP_INTERLEAVE_NONE,
          CU_TENSOR_MAP_SWIZZLE_128B, CU_TENSOR_MAP_L2_PROMOTION_L2_256B, CU_TENSOR_MAP_FLOAT_OOB_FILL_NONE);
    }
    {
      cuuint64_t dims[3] = {64, DM, 64}; cuuint64_t str[2] = {H_ * DH * 2, 128}; cuuint32_t box[3] = {64, 32, 4};
      enc(&P.wq, CU_TENSOR_MAP_DATA_TYPE_BFLOAT16, 3, d_in[3], dims, str, box, es, CU_TENSOR_MAP_INTERLEAVE_NONE,
          CU_TENSOR_MAP_SWIZZLE_128B, CU_TENSOR_MAP_L2_PROMOTION_L2_256B, CU_TENSOR_MAP_FLOAT_OOB_FILL_NONE);
    }
    {
      cuuint64_t dims[2] = {DM, H_ * DH}; cuuint64_t str[1] = {DM * 2}; cuuint32_t box[2] = {64, 256};
      enc(&P.wo, CU_TENSOR_MAP_DATA_TYPE_BFLOAT16, 2, d_in[4], dims, str, box, es, CU_TENSOR_MAP_INTERLEAVE_NONE,
          CU_TENSOR_MAP_SWIZZLE_128B, CU_TENSOR_MAP_L2_PROMOTION_L2_128B, CU_TENSOR_MAP_FLOAT_OOB_FILL_NONE);
    }
    for (int i = 0; i < 5; i++) cached[i] = d_in[i];
  }
  mha_fused_kernel<<<B_ * H_, NTHREADS, SMEM_TOTAL>>>(P, (__nv_bfloat16*)d_out);
}
```

```cpp
#include <cuda_runtime.h>
#include <cuda_bf16.h>
#include <cuda.h>
#include <stdint.h>

namespace {

constexpr int B_ = 8, SQ = 192, DM = 448, H_ = 16, SK = 1024, DH = 256;
constexpr int NTHREADS = 256;
constexpr int NSLOT = 7;
constexpr int SLOT_BYTES = 16384;
constexpr int Q_BYTES = 98304;
constexpr int QP_STAGE_BYTES = 28672;
constexpr int QP_X_BYTES = 12288;
constexpr int QP_CHUNKS = 14;
constexpr int N_KV = 64;
constexpr int OFF_RING = Q_BYTES;
constexpr int OFF_P2 = OFF_RING + NSLOT * SLOT_BYTES;
constexpr int OFF_M2 = OFF_P2 + 16384;
constexpr int OFF_BAR = OFF_M2 + 1024;
constexpr int SMEM_TOTAL = OFF_BAR + 512;

__device__ __align__(1024) unsigned char g_part[B_ * 4 * 32 * 24576];
__device__ unsigned int g_cnt[B_ * 8];

__device__ __forceinline__ uint32_t smem_u32(const void* p) { return (uint32_t)__cvta_generic_to_shared(p); }
__device__ __forceinline__ void mbar_init(uint32_t a, int c) { asm volatile("mbarrier.init.shared::cta.b64 [%0], %1;" ::"r"(a), "r"(c)); }
__device__ __forceinline__ void mbar_expect(uint32_t a, int bytes) {
  asm volatile("mbarrier.arrive.expect_tx.shared::cta.b64 _, [%0], %1;" ::"r"(a), "r"(bytes) : "memory");
}
__device__ __forceinline__ void mbar_arrive(uint32_t a) {
  asm volatile("mbarrier.arrive.shared::cta.b64 _, [%0];" ::"r"(a) : "memory");
}
__device__ __forceinline__ void mbar_wait(uint32_t a, int parity) {
  asm volatile(
      "{\n.reg .pred p;\n.reg .u32 c;\n"
      "mbarrier.try_wait.parity.shared::cta.b64 p, [%0], %1;\n"
      "@p bra LAB_DONE;\n"
      "mov.u32 c, 0;\n"
      "LAB_WAIT:\n"
      "mbarrier.try_wait.parity.shared::cta.b64 p, [%0], %1;\n"
      "@p bra LAB_DONE;\n"
      "add.u32 c, c, 1;\n"
      "setp.lt.u32 p, c, 4000000;\n"
      "@p bra LAB_WAIT;\n"
      "trap;\n"
      "LAB_DONE:\n}\n" ::"r"(a), "r"(parity) : "memory");
}
__device__ __forceinline__ void tma2(uint32_t dst, const CUtensorMap* m, int c0, int c1, uint32_t mbar) {
  asm volatile("cp.async.bulk.tensor.2d.shared::cluster.global.mbarrier::complete_tx::bytes [%0], [%1, {%3,%4}], [%2];"
               ::"r"(dst), "l"(m), "r"(mbar), "r"(c0), "r"(c1) : "memory");
}
__device__ __forceinline__ void tma3(uint32_t dst, const CUtensorMap* m, int c0, int c1, int c2, uint32_t mbar) {
  asm volatile("cp.async.bulk.tensor.3d.shared::cluster.global.mbarrier::complete_tx::bytes [%0], [%1, {%3,%4,%5}], [%2];"
               ::"r"(dst), "l"(m), "r"(mbar), "r"(c0), "r"(c1), "r"(c2) : "memory");
}
__device__ __forceinline__ void sts_v4(uint32_t a, uint32_t x, uint32_t y, uint32_t z, uint32_t w) {
  asm volatile("st.shared.v4.b32 [%0], {%1,%2,%3,%4};" ::"r"(a), "r"(x), "r"(y), "r"(z), "r"(w) : "memory");
}
__device__ __forceinline__ float bf_lo(uint32_t w) { return __uint_as_float(w << 16); }
__device__ __forceinline__ float bf_hi(uint32_t w) { return __uint_as_float(w & 0xffff0000u); }
__device__ __forceinline__ uint32_t arrive_cnt(uint32_t a, int lane) {
  uint32_t old;
  asm volatile("{\n.reg .pred p;\nsetp.eq.s32 p, %2, 0;\nmov.u32 %0, 0;\n@p atom.relaxed.cta.shared::cta.inc.u32 %0, [%1], 7;\n}\n"
               : "=r"(old) : "r"(a), "r"(lane) : "memory");
  return old;
}
__device__ __forceinline__ void wg_fence() { asm volatile("wgmma.fence.sync.aligned;" ::: "memory"); }
__device__ __forceinline__ void wg_commit() { asm volatile("wgmma.commit_group.sync.aligned;" ::: "memory"); }
template <int N> __device__ __forceinline__ void wg_wait() { asm volatile("wgmma.wait_group.sync.aligned %0;" ::"n"(N) : "memory"); }
__device__ __forceinline__ void fence_async_smem() { asm volatile("fence.proxy.async.shared::cta;" ::: "memory"); }
__device__ __forceinline__ void bar_arrive(int id, int n) { asm volatile("bar.arrive %0, %1;" ::"r"(id), "r"(n) : "memory"); }
#define PP_WAIT() bar_sync(1 + wg, 256)
#define PP_PASS() bar_arrive(2 - wg, 256)
__device__ __forceinline__ void bar_sync(int id, int n) { asm volatile("bar.sync %0, %1;" ::"r"(id), "r"(n) : "memory"); }
template <int N> __device__ __forceinline__ void fence_regs(float (&d)[N]) {
#pragma unroll
  for (int i = 0; i < N; i++) asm volatile("" : "+f"(d[i])::"memory");
}
__device__ __forceinline__ uint32_t pack_bf16(float lo, float hi) {
  uint32_t r;
  asm("cvt.rn.bf16x2.f32 %0, %1, %2;" : "=r"(r) : "f"(hi), "f"(lo));
  return r;
}
__device__ __forceinline__ float ex2(float x) {
  float y;
  asm("ex2.approx.ftz.f32 %0, %1;" : "=f"(y) : "f"(x));
  return y;
}
__device__ __forceinline__ void stsm4(uint32_t addr, uint32_t r0, uint32_t r1, uint32_t r2, uint32_t r3) {
  asm volatile("stmatrix.sync.aligned.m8n8.x4.shared.b16 [%0], {%1,%2,%3,%4};" ::"r"(addr), "r"(r0), "r"(r1), "r"(r2), "r"(r3) : "memory");
}
__device__ __forceinline__ void sts_f32(uint32_t a, float v) { asm volatile("st.shared.f32 [%0], %1;" ::"r"(a), "f"(v) : "memory"); }
__device__ __forceinline__ uint32_t lds_u32(uint32_t a) { uint32_t v; asm volatile("ld.shared.u32 %0, [%1];" : "=r"(v) : "r"(a) : "memory"); return v; }
__device__ __forceinline__ float lds_f32(uint32_t a) { float v; asm volatile("ld.shared.f32 %0, [%1];" : "=f"(v) : "r"(a) : "memory"); return v; }
__device__ __forceinline__ uint32_t dlo(uint32_t addr, uint32_t lbo) { return ((addr & 0x3FFFFu) >> 4) | ((lbo >> 4) << 16); }
constexpr uint32_t HI128 = (1024u >> 4) | (1u << 30);
constexpr uint32_t HI64 = (512u >> 4) | (2u << 30);

template <uint32_t HA, uint32_t HB>
__device__ __forceinline__ void wgmma_n256_ss_tb(float (&d)[128], uint32_t da, uint32_t db, int scale_d) {
  asm volatile("{\n.reg .pred p;\n.reg .b64 da, db;\nsetp.ne.b32 p, %130, 0;\nmov.b64 da, {%128, %131};\nmov.b64 db, {%129, %132};\n"
    "wgmma.mma_async.sync.aligned.m64n256k16.f32.bf16.bf16 {%0, %1, %2, %3, %4, %5, %6, %7, %8, %9, %10, %11, %12, %13, %14, %15, %16, %17, %18, %19, %20, %21, %22, %23, %24, %25, %26, %27, %28, %29, %30, %31, %32, %33, %34, %35, %36, %37, %38, %39, %40, %41, %42, %43, %44, %45, %46, %47, %48, %49, %50, %51, %52, %53, %54, %55, %56, %57, %58, %59, %60, %61, %62, %63, %64, %65, %66, %67, %68, %69, %70, %71, %72, %73, %74, %75, %76, %77, %78, %79, %80, %81, %82, %83, %84, %85, %86, %87, %88, %89, %90, %91, %92, %93, %94, %95, %96, %97, %98, %99, %100, %101, %102, %103, %104, %105, %106, %107, %108, %109, %110, %111, %112, %113, %114, %115, %116, %117, %118, %119, %120, %121, %122, %123, %124, %125, %126, %127}, da, db, p, 1, 1, 0, 1;\n}\n"
    : "+f"(d[0]), "+f"(d[1]), "+f"(d[2]), "+f"(d[3]), "+f"(d[4]), "+f"(d[5]), "+f"(d[6]), "+f"(d[7]), "+f"(d[8]), "+f"(d[9]), "+f"(d[10]), "+f"(d[11]), "+f"(d[12]), "+f"(d[13]), "+f"(d[14]), "+f"(d[15]), "+f"(d[16]), "+f"(d[17]), "+f"(d[18]), "+f"(d[19]), "+f"(d[20]), "+f"(d[21]), "+f"(d[22]), "+f"(d[23]), "+f"(d[24]), "+f"(d[25]), "+f"(d[26]), "+f"(d[27]), "+f"(d[28]), "+f"(d[29]), "+f"(d[30]), "+f"(d[31]), "+f"(d[32]), "+f"(d[33]), "+f"(d[34]), "+f"(d[35]), "+f"(d[36]), "+f"(d[37]), "+f"(d[38]), "+f"(d[39]), "+f"(d[40]), "+f"(d[41]), "+f"(d[42]), "+f"(d[43]), "+f"(d[44]), "+f"(d[45]), "+f"(d[46]), "+f"(d[47]), "+f"(d[48]), "+f"(d[49]), "+f"(d[50]), "+f"(d[51]), "+f"(d[52]), "+f"(d[53]), "+f"(d[54]), "+f"(d[55]), "+f"(d[56]), "+f"(d[57]), "+f"(d[58]), "+f"(d[59]), "+f"(d[60]), "+f"(d[61]), "+f"(d[62]), "+f"(d[63]), "+f"(d[64]), "+f"(d[65]), "+f"(d[66]), "+f"(d[67]), "+f"(d[68]), "+f"(d[69]), "+f"(d[70]), "+f"(d[71]), "+f"(d[72]), "+f"(d[73]), "+f"(d[74]), "+f"(d[75]), "+f"(d[76]), "+f"(d[77]), "+f"(d[78]), "+f"(d[79]), "+f"(d[80]), "+f"(d[81]), "+f"(d[82]), "+f"(d[83]), "+f"(d[84]), "+f"(d[85]), "+f"(d[86]), "+f"(d[87]), "+f"(d[88]), "+f"(d[89]), "+f"(d[90]), "+f"(d[91]), "+f"(d[92]), "+f"(d[93]), "+f"(d[94]), "+f"(d[95]), "+f"(d[96]), "+f"(d[97]), "+f"(d[98]), "+f"(d[99]), "+f"(d[100]), "+f"(d[101]), "+f"(d[102]), "+f"(d[103]), "+f"(d[104]), "+f"(d[105]), "+f"(d[106]), "+f"(d[107]), "+f"(d[108]), "+f"(d[109]), "+f"(d[110]), "+f"(d[111]), "+f"(d[112]), "+f"(d[113]), "+f"(d[114]), "+f"(d[115]), "+f"(d[116]), "+f"(d[117]), "+f"(d[118]), "+f"(d[119]), "+f"(d[120]), "+f"(d[121]), "+f"(d[122]), "+f"(d[123]), "+f"(d[124]), "+f"(d[125]), "+f"(d[126]), "+f"(d[127])
    : "r"(da), "r"(db), "r"(scale_d), "n"(HA), "n"(HB));
}
template <uint32_t HA, uint32_t HB>
__device__ __forceinline__ void wgmma_n64_ss(float (&d)[32], uint32_t da, uint32_t db, int scale_d) {
  asm volatile("{\n.reg .pred p;\n.reg .b64 da, db;\nsetp.ne.b32 p, %34, 0;\nmov.b64 da, {%32, %35};\nmov.b64 db, {%33, %36};\n"
    "wgmma.mma_async.sync.aligned.m64n64k16.f32.bf16.bf16 {%0, %1, %2, %3, %4, %5, %6, %7, %8, %9, %10, %11, %12, %13, %14, %15, %16, %17, %18, %19, %20, %21, %22, %23, %24, %25, %26, %27, %28, %29, %30, %31}, da, db, p, 1, 1, 0, 0;\n}\n"
    : "+f"(d[0]), "+f"(d[1]), "+f"(d[2]), "+f"(d[3]), "+f"(d[4]), "+f"(d[5]), "+f"(d[6]), "+f"(d[7]), "+f"(d[8]), "+f"(d[9]), "+f"(d[10]), "+f"(d[11]), "+f"(d[12]), "+f"(d[13]), "+f"(d[14]), "+f"(d[15]), "+f"(d[16]), "+f"(d[17]), "+f"(d[18]), "+f"(d[19]), "+f"(d[20]), "+f"(d[21]), "+f"(d[22]), "+f"(d[23]), "+f"(d[24]), "+f"(d[25]), "+f"(d[26]), "+f"(d[27]), "+f"(d[28]), "+f"(d[29]), "+f"(d[30]), "+f"(d[31])
    : "r"(da), "r"(db), "r"(scale_d), "n"(HA), "n"(HB));
}
template <uint32_t HB>
__device__ __forceinline__ void wgmma_n256_rs_tb(float (&d)[128], uint32_t a0, uint32_t a1, uint32_t a2, uint32_t a3, uint32_t db, int scale_d) {
  asm volatile("{\n.reg .pred p;\n.reg .b64 db;\nsetp.ne.b32 p, %133, 0;\nmov.b64 db, {%132, %134};\n"
    "wgmma.mma_async.sync.aligned.m64n256k16.f32.bf16.bf16 {%0, %1, %2, %3, %4, %5, %6, %7, %8, %9, %10, %11, %12, %13, %14, %15, %16, %17, %18, %19, %20, %21, %22, %23, %24, %25, %26, %27, %28, %29, %30, %31, %32, %33, %34, %35, %36, %37, %38, %39, %40, %41, %42, %43, %44, %45, %46, %47, %48, %49, %50, %51, %52, %53, %54, %55, %56, %57, %58, %59, %60, %61, %62, %63, %64, %65, %66, %67, %68, %69, %70, %71, %72, %73, %74, %75, %76, %77, %78, %79, %80, %81, %82, %83, %84, %85, %86, %87, %88, %89, %90, %91, %92, %93, %94, %95, %96, %97, %98, %99, %100, %101, %102, %103, %104, %105, %106, %107, %108, %109, %110, %111, %112, %113, %114, %115, %116, %117, %118, %119, %120, %121, %122, %123, %124, %125, %126, %127}, {%128, %129, %130, %131}, db, p, 1, 1, 1;\n}\n"
    : "+f"(d[0]), "+f"(d[1]), "+f"(d[2]), "+f"(d[3]), "+f"(d[4]), "+f"(d[5]), "+f"(d[6]), "+f"(d[7]), "+f"(d[8]), "+f"(d[9]), "+f"(d[10]), "+f"(d[11]), "+f"(d[12]), "+f"(d[13]), "+f"(d[14]), "+f"(d[15]), "+f"(d[16]), "+f"(d[17]), "+f"(d[18]), "+f"(d[19]), "+f"(d[20]), "+f"(d[21]), "+f"(d[22]), "+f"(d[23]), "+f"(d[24]), "+f"(d[25]), "+f"(d[26]), "+f"(d[27]), "+f"(d[28]), "+f"(d[29]), "+f"(d[30]), "+f"(d[31]), "+f"(d[32]), "+f"(d[33]), "+f"(d[34]), "+f"(d[35]), "+f"(d[36]), "+f"(d[37]), "+f"(d[38]), "+f"(d[39]), "+f"(d[40]), "+f"(d[41]), "+f"(d[42]), "+f"(d[43]), "+f"(d[44]), "+f"(d[45]), "+f"(d[46]), "+f"(d[47]), "+f"(d[48]), "+f"(d[49]), "+f"(d[50]), "+f"(d[51]), "+f"(d[52]), "+f"(d[53]), "+f"(d[54]), "+f"(d[55]), "+f"(d[56]), "+f"(d[57]), "+f"(d[58]), "+f"(d[59]), "+f"(d[60]), "+f"(d[61]), "+f"(d[62]), "+f"(d[63]), "+f"(d[64]), "+f"(d[65]), "+f"(d[66]), "+f"(d[67]), "+f"(d[68]), "+f"(d[69]), "+f"(d[70]), "+f"(d[71]), "+f"(d[72]), "+f"(d[73]), "+f"(d[74]), "+f"(d[75]), "+f"(d[76]), "+f"(d[77]), "+f"(d[78]), "+f"(d[79]), "+f"(d[80]), "+f"(d[81]), "+f"(d[82]), "+f"(d[83]), "+f"(d[84]), "+f"(d[85]), "+f"(d[86]), "+f"(d[87]), "+f"(d[88]), "+f"(d[89]), "+f"(d[90]), "+f"(d[91]), "+f"(d[92]), "+f"(d[93]), "+f"(d[94]), "+f"(d[95]), "+f"(d[96]), "+f"(d[97]), "+f"(d[98]), "+f"(d[99]), "+f"(d[100]), "+f"(d[101]), "+f"(d[102]), "+f"(d[103]), "+f"(d[104]), "+f"(d[105]), "+f"(d[106]), "+f"(d[107]), "+f"(d[108]), "+f"(d[109]), "+f"(d[110]), "+f"(d[111]), "+f"(d[112]), "+f"(d[113]), "+f"(d[114]), "+f"(d[115]), "+f"(d[116]), "+f"(d[117]), "+f"(d[118]), "+f"(d[119]), "+f"(d[120]), "+f"(d[121]), "+f"(d[122]), "+f"(d[123]), "+f"(d[124]), "+f"(d[125]), "+f"(d[126]), "+f"(d[127])
    : "r"(a0), "r"(a1), "r"(a2), "r"(a3), "r"(db), "r"(scale_d), "n"(HB));
}
template <uint32_t HB>
__device__ __forceinline__ void wgmma_n64_rs_tb(float (&d)[32], uint32_t a0, uint32_t a1, uint32_t a2, uint32_t a3, uint32_t db, int scale_d) {
  asm volatile("{\n.reg .pred p;\n.reg .b64 db;\nsetp.ne.b32 p, %37, 0;\nmov.b64 db, {%36, %38};\n"
    "wgmma.mma_async.sync.aligned.m64n64k16.f32.bf16.bf16 {%0, %1, %2, %3, %4, %5, %6, %7, %8, %9, %10, %11, %12, %13, %14, %15, %16, %17, %18, %19, %20, %21, %22, %23, %24, %25, %26, %27, %28, %29, %30, %31}, {%32, %33, %34, %35}, db, p, 1, 1, 1;\n}\n"
    : "+f"(d[0]), "+f"(d[1]), "+f"(d[2]), "+f"(d[3]), "+f"(d[4]), "+f"(d[5]), "+f"(d[6]), "+f"(d[7]), "+f"(d[8]), "+f"(d[9]), "+f"(d[10]), "+f"(d[11]), "+f"(d[12]), "+f"(d[13]), "+f"(d[14]), "+f"(d[15]), "+f"(d[16]), "+f"(d[17]), "+f"(d[18]), "+f"(d[19]), "+f"(d[20]), "+f"(d[21]), "+f"(d[22]), "+f"(d[23]), "+f"(d[24]), "+f"(d[25]), "+f"(d[26]), "+f"(d[27]), "+f"(d[28]), "+f"(d[29]), "+f"(d[30]), "+f"(d[31])
    : "r"(a0), "r"(a1), "r"(a2), "r"(a3), "r"(db), "r"(scale_d), "n"(HB));
}
template <uint32_t HA, uint32_t HB>
__device__ __forceinline__ void wgmma_n64_ss_tb(float (&d)[32], uint32_t da, uint32_t db, int scale_d) {
  asm volatile("{\n.reg .pred p;\n.reg .b64 da, db;\nsetp.ne.b32 p, %34, 0;\nmov.b64 da, {%32, %35};\nmov.b64 db, {%33, %36};\n"
    "wgmma.mma_async.sync.aligned.m64n64k16.f32.bf16.bf16 {%0, %1, %2, %3, %4, %5, %6, %7, %8, %9, %10, %11, %12, %13, %14, %15, %16, %17, %18, %19, %20, %21, %22, %23, %24, %25, %26, %27, %28, %29, %30, %31}, da, db, p, 1, 1, 0, 1;\n}\n"
    : "+f"(d[0]), "+f"(d[1]), "+f"(d[2]), "+f"(d[3]), "+f"(d[4]), "+f"(d[5]), "+f"(d[6]), "+f"(d[7]), "+f"(d[8]), "+f"(d[9]), "+f"(d[10]), "+f"(d[11]), "+f"(d[12]), "+f"(d[13]), "+f"(d[14]), "+f"(d[15]), "+f"(d[16]), "+f"(d[17]), "+f"(d[18]), "+f"(d[19]), "+f"(d[20]), "+f"(d[21]), "+f"(d[22]), "+f"(d[23]), "+f"(d[24]), "+f"(d[25]), "+f"(d[26]), "+f"(d[27]), "+f"(d[28]), "+f"(d[29]), "+f"(d[30]), "+f"(d[31])
    : "r"(da), "r"(db), "r"(scale_d), "n"(HA), "n"(HB));
}
template <uint32_t HB>
__device__ __forceinline__ void wgmma_n128_rs_tb(float (&d)[64], uint32_t a0, uint32_t a1, uint32_t a2, uint32_t a3, uint32_t db, int scale_d) {
  asm volatile("{\n.reg .pred p;\n.reg .b64 db;\nsetp.ne.b32 p, %69, 0;\nmov.b64 db, {%68, %70};\n"
    "wgmma.mma_async.sync.aligned.m64n128k16.f32.bf16.bf16 {%0, %1, %2, %3, %4, %5, %6, %7, %8, %9, %10, %11, %12, %13, %14, %15, %16, %17, %18, %19, %20, %21, %22, %23, %24, %25, %26, %27, %28, %29, %30, %31, %32, %33, %34, %35, %36, %37, %38, %39, %40, %41, %42, %43, %44, %45, %46, %47, %48, %49, %50, %51, %52, %53, %54, %55, %56, %57, %58, %59, %60, %61, %62, %63}, {%64, %65, %66, %67}, db, p, 1, 1, 1;\n}\n"
    : "+f"(d[0]), "+f"(d[1]), "+f"(d[2]), "+f"(d[3]), "+f"(d[4]), "+f"(d[5]), "+f"(d[6]), "+f"(d[7]), "+f"(d[8]), "+f"(d[9]), "+f"(d[10]), "+f"(d[11]), "+f"(d[12]), "+f"(d[13]), "+f"(d[14]), "+f"(d[15]), "+f"(d[16]), "+f"(d[17]), "+f"(d[18]), "+f"(d[19]), "+f"(d[20]), "+f"(d[21]), "+f"(d[22]), "+f"(d[23]), "+f"(d[24]), "+f"(d[25]), "+f"(d[26]), "+f"(d[27]), "+f"(d[28]), "+f"(d[29]), "+f"(d[30]), "+f"(d[31]), "+f"(d[32]), "+f"(d[33]), "+f"(d[34]), "+f"(d[35]), "+f"(d[36]), "+f"(d[37]), "+f"(d[38]), "+f"(d[39]), "+f"(d[40]), "+f"(d[41]), "+f"(d[42]), "+f"(d[43]), "+f"(d[44]), "+f"(d[45]), "+f"(d[46]), "+f"(d[47]), "+f"(d[48]), "+f"(d[49]), "+f"(d[50]), "+f"(d[51]), "+f"(d[52]), "+f"(d[53]), "+f"(d[54]), "+f"(d[55]), "+f"(d[56]), "+f"(d[57]), "+f"(d[58]), "+f"(d[59]), "+f"(d[60]), "+f"(d[61]), "+f"(d[62]), "+f"(d[63])
    : "r"(a0), "r"(a1), "r"(a2), "r"(a3), "r"(db), "r"(scale_d), "n"(HB));
}
template <uint32_t HA, uint32_t HB>
__device__ __forceinline__ void wgmma_n128_ss_tb(float (&d)[64], uint32_t da, uint32_t db, int scale_d) {
  asm volatile("{\n.reg .pred p;\n.reg .b64 da, db;\nsetp.ne.b32 p, %66, 0;\nmov.b64 da, {%64, %67};\nmov.b64 db, {%65, %68};\n"
    "wgmma.mma_async.sync.aligned.m64n128k16.f32.bf16.bf16 {%0, %1, %2, %3, %4, %5, %6, %7, %8, %9, %10, %11, %12, %13, %14, %15, %16, %17, %18, %19, %20, %21, %22, %23, %24, %25, %26, %27, %28, %29, %30, %31, %32, %33, %34, %35, %36, %37, %38, %39, %40, %41, %42, %43, %44, %45, %46, %47, %48, %49, %50, %51, %52, %53, %54, %55, %56, %57, %58, %59, %60, %61, %62, %63}, da, db, p, 1, 1, 0, 1;\n}\n"
    : "+f"(d[0]), "+f"(d[1]), "+f"(d[2]), "+f"(d[3]), "+f"(d[4]), "+f"(d[5]), "+f"(d[6]), "+f"(d[7]), "+f"(d[8]), "+f"(d[9]), "+f"(d[10]), "+f"(d[11]), "+f"(d[12]), "+f"(d[13]), "+f"(d[14]), "+f"(d[15]), "+f"(d[16]), "+f"(d[17]), "+f"(d[18]), "+f"(d[19]), "+f"(d[20]), "+f"(d[21]), "+f"(d[22]), "+f"(d[23]), "+f"(d[24]), "+f"(d[25]), "+f"(d[26]), "+f"(d[27]), "+f"(d[28]), "+f"(d[29]), "+f"(d[30]), "+f"(d[31]), "+f"(d[32]), "+f"(d[33]), "+f"(d[34]), "+f"(d[35]), "+f"(d[36]), "+f"(d[37]), "+f"(d[38]), "+f"(d[39]), "+f"(d[40]), "+f"(d[41]), "+f"(d[42]), "+f"(d[43]), "+f"(d[44]), "+f"(d[45]), "+f"(d[46]), "+f"(d[47]), "+f"(d[48]), "+f"(d[49]), "+f"(d[50]), "+f"(d[51]), "+f"(d[52]), "+f"(d[53]), "+f"(d[54]), "+f"(d[55]), "+f"(d[56]), "+f"(d[57]), "+f"(d[58]), "+f"(d[59]), "+f"(d[60]), "+f"(d[61]), "+f"(d[62]), "+f"(d[63])
    : "r"(da), "r"(db), "r"(scale_d), "n"(HA), "n"(HB));
}
template <uint32_t HA, uint32_t HB>
__device__ __forceinline__ void wgmma_n32_ss_tb(float (&d)[16], uint32_t da, uint32_t db, int scale_d) {
  asm volatile("{\n.reg .pred p;\n.reg .b64 da, db;\nsetp.ne.b32 p, %18, 0;\nmov.b64 da, {%16, %19};\nmov.b64 db, {%17, %20};\n"
    "wgmma.mma_async.sync.aligned.m64n32k16.f32.bf16.bf16 {%0, %1, %2, %3, %4, %5, %6, %7, %8, %9, %10, %11, %12, %13, %14, %15}, da, db, p, 1, 1, 0, 1;\n}\n"
    : "+f"(d[0]), "+f"(d[1]), "+f"(d[2]), "+f"(d[3]), "+f"(d[4]), "+f"(d[5]), "+f"(d[6]), "+f"(d[7]), "+f"(d[8]), "+f"(d[9]), "+f"(d[10]), "+f"(d[11]), "+f"(d[12]), "+f"(d[13]), "+f"(d[14]), "+f"(d[15])
    : "r"(da), "r"(db), "r"(scale_d), "n"(HA), "n"(HB));
}


struct Params {
  CUtensorMap x, wq, k, v, wo, wo3;
};

constexpr float CS = 0.0625f * 1.4426950408889634f;

__device__ __forceinline__ void issue_seq(const Params& P, int n, uint32_t sbase, int bh, int h) {
  const uint32_t slot = (uint32_t)n % NSLOT;
  const uint32_t bar = sbase + OFF_BAR + slot * 8;
  const uint32_t dst = sbase + OFF_RING + slot * SLOT_BYTES;
  mbar_expect(bar, SLOT_BYTES);
  if (n < N_KV) {
    const int row = bh * SK + (n >> 2) * 64;
    if (n & 2) tma3(dst, &P.v, 0, row + (n & 1) * 32, 0, bar);
    else tma3(dst, &P.k, 0, row, (n & 1) * 2, bar);
  } else {
    const int m = n - N_KV;
    if (m < 12) tma3(dst, &P.wo3, 0, h * DH + (m & 3) * 64, (m >> 2) * 2, bar);
    else tma2(dst, &P.wo, 384, h * DH + (m - 12) * 128, bar);
  }
}
__device__ __forceinline__ constexpr int wo_slot(int m) { return m < 7 ? (m + 1) % 7 : (m == 7 ? 7 : (m - 7) % 7); }
__device__ __forceinline__ constexpr int wo_par(int m) { return m < 6 ? 1 : 0; }
__device__ __forceinline__ void issue_wo(const Params& P, int m, uint32_t sbase, int h) {
  const uint32_t slot = wo_slot(m);
  const uint32_t bar = sbase + OFF_BAR + slot * 8;
  const uint32_t dst = sbase + OFF_RING + slot * SLOT_BYTES;
  mbar_expect(bar, SLOT_BYTES);
  if (m < 12) tma3(dst, &P.wo3, 0, h * DH + (m & 3) * 64, (m >> 2) * 2, bar);
  else tma2(dst, &P.wo, 384, h * DH + (m - 12) * 128, bar);
}
__device__ __forceinline__ uint32_t qp_stage_off(int st) { return st < 4 ? OFF_RING + st * QP_STAGE_BYTES : (st - 4) * QP_STAGE_BYTES; }
__device__ __forceinline__ void issue_qp(const Params& P, int c, uint32_t sbase, int b, int h) {
  const int st = c < 7 ? c : c - 7;
  const uint32_t bar = sbase + OFF_BAR + 64 + st * 8;
  const uint32_t dst = sbase + qp_stage_off(st);
  mbar_expect(bar, QP_STAGE_BYTES);
  tma2(dst, &P.x, c * 32, b * SQ, bar);
  tma3(dst + QP_X_BYTES, &P.wq, 0, c * 32, h * 4, bar);
}

__device__ __forceinline__ void qk_half(float (&s)[32], uint32_t dq, uint32_t dk, int first) {
#pragma unroll
  for (int kk = 0; kk < 8; kk++) {
    const uint32_t off = (kk >> 2) * 512 + (kk & 3) * 2;
    wgmma_n64_ss<HI128, HI128>(s, dq + off, dk + off, !(first && kk == 0));
  }
}
__device__ __forceinline__ void pv2_half(float (&o2)[64], uint32_t dp, uint32_t dv) {
  wgmma_n128_ss_tb<HI128, HI128>(o2, dp, dv, 1);
  wgmma_n128_ss_tb<HI128, HI128>(o2, dp + 2, dv + 128, 1);
}

__device__ __forceinline__ void row_max(const float (&s)[32], float& mx0, float& mx1) {
  mx0 = fmaxf(s[0], s[1]); mx1 = fmaxf(s[2], s[3]);
#pragma unroll
  for (int i = 1; i < 8; i++) {
    mx0 = fmaxf(mx0, fmaxf(s[4 * i], s[4 * i + 1]));
    mx1 = fmaxf(mx1, fmaxf(s[4 * i + 2], s[4 * i + 3]));
  }
  mx0 = fmaxf(mx0, __shfl_xor_sync(0xffffffffu, mx0, 1));
  mx1 = fmaxf(mx1, __shfl_xor_sync(0xffffffffu, mx1, 1));
  mx0 = fmaxf(mx0, __shfl_xor_sync(0xffffffffu, mx0, 2));
  mx1 = fmaxf(mx1, __shfl_xor_sync(0xffffffffu, mx1, 2));
}
template <int NO>
__device__ __forceinline__ void rescale(float mn0, float mn1, float& ms0, float& ms1, float& l0, float& l1, float (&o)[NO]) {
  if (__any_sync(0xffffffffu, (mn0 > ms0) || (mn1 > ms1))) {
    const float a0 = ex2(ms0 - mn0), a1 = ex2(ms1 - mn1);
    l0 *= a0; l1 *= a1;
#pragma unroll
    for (int i = 0; i < NO / 4; i++) {
      o[4 * i] *= a0; o[4 * i + 1] *= a0; o[4 * i + 2] *= a1; o[4 * i + 3] *= a1;
    }
    ms0 = mn0; ms1 = mn1;
  }
}
__device__ __forceinline__ void exp_pack(const float (&s)[32], uint32_t (&p)[16], float ms0, float ms1, float& l0, float& l1) {
#pragma unroll
  for (int i = 0; i < 8; i++) {
    const float e0 = ex2(fmaf(s[4 * i], CS, -ms0)), e1 = ex2(fmaf(s[4 * i + 1], CS, -ms0));
    const float e2 = ex2(fmaf(s[4 * i + 2], CS, -ms1)), e3 = ex2(fmaf(s[4 * i + 3], CS, -ms1));
    l0 += e0 + e1; l1 += e2 + e3;
    p[2 * i] = pack_bf16(e0, e1);
    p[2 * i + 1] = pack_bf16(e2, e3);
  }
}

__global__ void __launch_bounds__(NTHREADS, 1)
mha_fused_kernel(const __grid_constant__ Params P, __nv_bfloat16* __restrict__ out) {
  extern __shared__ __align__(1024) char smem_raw[];
  const uint32_t sbase = smem_u32(smem_raw);
  const int tid = threadIdx.x;
  const int lane = tid & 31;
  const int warp = tid >> 5;
  const int wg = __shfl_sync(0xffffffffu, tid >> 7, 0);
  const int bh = blockIdx.x;
  const int b = bh >> 4, h = bh & 15;
  const uint32_t bar_full = sbase + OFF_BAR;
  const uint32_t bar_qp = sbase + OFF_BAR + 64;
  const uint32_t bar_p2 = sbase + OFF_BAR + 120;
  const uint32_t bar_o2 = sbase + OFF_BAR + 136;
  const uint32_t cnt_k = sbase + OFF_BAR + 144;
  const uint32_t cnt_v = sbase + OFF_BAR + 152;
  const uint32_t cnt_qp = sbase + OFF_BAR + 160;
  const uint32_t cnt_wo = sbase + OFF_BAR + 204;

  if (tid == 64) {
    asm volatile("cp.async.ca.shared.global [%0], [%1], 4;" ::"r"(sbase + OFF_BAR + 320), "l"(&g_cnt[b * 8 + 4]) : "memory");
  }
  if (tid == 32) {
    asm volatile("prefetch.tensormap [%0];" ::"l"(&P.x) : "memory");
    asm volatile("prefetch.tensormap [%0];" ::"l"(&P.wq) : "memory");
    asm volatile("prefetch.tensormap [%0];" ::"l"(&P.k) : "memory");
    asm volatile("prefetch.tensormap [%0];" ::"l"(&P.v) : "memory");
  }
  if (tid == 0) {
    for (int i = 0; i < NSLOT + 1; i++) mbar_init(bar_full + i * 8, 1);
    for (int i = 0; i < 7; i++) mbar_init(bar_qp + i * 8, 1);
    for (int i = 0; i < 2; i++) mbar_init(bar_p2 + i * 8, 128);
    mbar_init(bar_o2, 256);
    for (int i = 0; i < 23; i++) asm volatile("st.shared.u32 [%0], %1;" ::"r"(cnt_k + i * 4), "r"(0) : "memory");
    asm volatile("fence.mbarrier_init.release.cluster;" ::: "memory");
    fence_async_smem();
    for (int c = 0; c < 7; c++) issue_qp(P, c, sbase, b, h);
  }
  __syncthreads();

  float o[128], o2[64];
  const int r = (warp & 3) * 16 + (lane & 7) + ((lane >> 3) & 1) * 8;
  {
    uint32_t oldq = 0;
#pragma unroll 1
    for (int c = 0; c < QP_CHUNKS; c++) {
      const int st = c < 7 ? c : c - 7;
      mbar_wait(bar_qp + st * 8, c >= 7);
      const uint32_t so = sbase + qp_stage_off(st);
      const uint32_t xa = dlo(so + wg * 4096, 16);
      const uint32_t x2 = dlo(so + 8192, 16);
      const uint32_t wa = dlo(so + QP_X_BYTES, 4096);
      wg_fence();
      wgmma_n256_ss_tb<HI64, HI128>(o, xa, wa, c > 0);
      wgmma_n256_ss_tb<HI64, HI128>(o, xa + 2, wa + 128, 1);
      wgmma_n128_ss_tb<HI64, HI128>(o2, x2, wa + wg * 512, c > 0);
      wgmma_n128_ss_tb<HI64, HI128>(o2, x2 + 2, wa + wg * 512 + 128, 1);
      wg_commit();
      if (c >= 2 && c < 9) { if (oldq == 7u) issue_qp(P, c + 5, sbase, b, h); }
      else if (c >= 9 && c < 13) {
        if (oldq == 7u) {
          if (c > 9) issue_seq(P, 2 * (c - 9) - 1, sbase, bh, h);
          issue_seq(P, 2 * (c - 9), sbase, bh, h);
        }
      }
      __syncwarp();
      if (c > 0) {
        wg_wait<1>();
        const int pc = c - 1;
        if (pc < 11) oldq = arrive_cnt(cnt_qp + pc * 4, lane);
      }
    }
    wg_wait<0>();
    fence_regs(o); fence_regs(o2);
    asm volatile("cp.async.wait_all;" ::: "memory");
    __syncthreads();
    const uint32_t qrow = sbase + wg * 32768 + r * 128;
#pragma unroll
    for (int j = 0; j < 32; j += 2) {
      const int cg = j + (lane >> 4);
      const uint32_t addr = qrow + (cg >> 3) * 8192 + (((cg & 7) ^ (r & 7)) << 4);
      stsm4(addr, pack_bf16(o[4 * j], o[4 * j + 1]), pack_bf16(o[4 * j + 2], o[4 * j + 3]),
            pack_bf16(o[4 * j + 4], o[4 * j + 5]), pack_bf16(o[4 * j + 6], o[4 * j + 7]));
    }
    const uint32_t q2row = sbase + 65536 + wg * 16384 + r * 128;
#pragma unroll
    for (int j = 0; j < 16; j += 2) {
      const int cg = j + (lane >> 4);
      const uint32_t addr = q2row + (cg >> 3) * 8192 + (((cg & 7) ^ (r & 7)) << 4);
      stsm4(addr, pack_bf16(o2[4 * j], o2[4 * j + 1]), pack_bf16(o2[4 * j + 2], o2[4 * j + 3]),
            pack_bf16(o2[4 * j + 4], o2[4 * j + 5]), pack_bf16(o2[4 * j + 6], o2[4 * j + 7]));
    }
    fence_async_smem();
    __syncthreads();
  }

  float ms0 = -INFINITY, ms1 = -INFINITY, l0 = 0.f, l1 = 0.f;
  float ns0 = -INFINITY, ns1 = -INFINITY, n0 = 0.f, n1 = 0.f;
#pragma unroll
  for (int i = 0; i < 128; i++) o[i] = 0.f;
#pragma unroll
  for (int i = 0; i < 64; i++) o2[i] = 0.f;
  const uint32_t qa = dlo(sbase + wg * 32768, 16);
  const uint32_t q2a = dlo(sbase + 65536, 16);
  const uint32_t m2row = sbase + OFF_M2 + ((warp & 3) * 16 + (lane >> 2)) * 4;
  int slot = 0, ph = 0;
  uint32_t oldv = 0;
  if (wg == 1) bar_arrive(1, 256);
#pragma unroll 1
  for (int j = 0; j < 16; j++) {
    const int s0 = slot, p0 = ph;
    int s1 = s0 + 1, p1 = p0; if (s1 == NSLOT) { s1 = 0; p1 ^= 1; }
    int s2 = s1 + 1, p2 = p1; if (s2 == NSLOT) { s2 = 0; p2 ^= 1; }
    int s3 = s2 + 1, p3 = p2; if (s3 == NSLOT) { s3 = 0; p3 ^= 1; }
    slot = s3 + 1; ph = p3; if (slot == NSLOT) { slot = 0; ph ^= 1; }
    const uint32_t kA = dlo(sbase + OFF_RING, 16) + s0 * 1024, kB = dlo(sbase + OFF_RING, 16) + s1 * 1024;
    const uint32_t vA = dlo(sbase + OFF_RING, 4096) + s2 * 1024, vB = dlo(sbase + OFF_RING, 4096) + s3 * 1024;
    const uint32_t p2a = sbase + OFF_P2 + (j & 1) * 8192;
    const uint32_t dp2 = dlo(sbase + OFF_P2, 16) + (j & 1) * 512;
    const bool own = ((j & 1) == wg);
    float s[32];
    uint32_t p[16];
    float mx0, mx1;
    mbar_wait(bar_full + s0 * 8, p0);
    if (own) {
      PP_WAIT();
      wg_fence();
      qk_half(s, q2a, kA, 1);
      mbar_wait(bar_full + s1 * 8, p1);
      wg_fence();
      qk_half(s, q2a + 1024, kB, 0);
      wg_commit();
      PP_PASS();
      if (oldv == 7u) { issue_seq(P, 4 * j + 5, sbase, bh, h); issue_seq(P, 4 * j + 6, sbase, bh, h); }
      __syncwarp();
      wg_wait<0>();
      fence_regs(s);
      row_max(s, mx0, mx1);
      rescale<64>(fmaxf(ns0, mx0 * CS), fmaxf(ns1, mx1 * CS), ns0, ns1, n0, n1, o2);
      exp_pack(s, p, ns0, ns1, n0, n1);
#pragma unroll
      for (int jj = 0; jj < 8; jj += 2) {
        const int cg = jj + (lane >> 4);
        stsm4(p2a + r * 128 + ((cg ^ (r & 7)) << 4), p[2 * jj], p[2 * jj + 1], p[2 * jj + 2], p[2 * jj + 3]);
      }
      if ((lane & 3) == 0) { sts_f32(m2row + (j & 1) * 256, ns0); sts_f32(m2row + (j & 1) * 256 + 32, ns1); }
      fence_async_smem();
      mbar_arrive(bar_p2 + (j & 1) * 8);
      PP_WAIT();
      wg_fence();
      qk_half(s, qa, kA, 1);
      qk_half(s, qa + 1024, kB, 0);
      wg_commit();
      mbar_wait(bar_p2 + (j & 1) * 8, (j >> 1) & 1);
      mbar_wait(bar_full + s2 * 8, p2);
      wg_fence();
      pv2_half(o2, dp2, vA + wg * 512);
      mbar_wait(bar_full + s3 * 8, p3);
      wg_fence();
      pv2_half(o2, dp2 + 4, vB + wg * 512);
      wg_commit();
      PP_PASS();
      wg_wait<1>();
      fence_regs(s);
    } else {
      PP_WAIT();
      wg_fence();
      qk_half(s, qa, kA, 1);
      mbar_wait(bar_full + s1 * 8, p1);
      wg_fence();
      qk_half(s, qa + 1024, kB, 0);
      wg_commit();
      PP_PASS();
      if (oldv == 7u) { issue_seq(P, 4 * j + 5, sbase, bh, h); issue_seq(P, 4 * j + 6, sbase, bh, h); }
      __syncwarp();
      wg_wait<0>();
      fence_regs(s);
    }
    const uint32_t oldk = arrive_cnt(cnt_k + (j & 1) * 4, lane);
    row_max(s, mx0, mx1);
    if (oldk == 7u) { issue_seq(P, 4 * j + 7, sbase, bh, h); issue_seq(P, 4 * j + 8, sbase, bh, h); }
    __syncwarp();
    rescale<128>(fmaxf(ms0, mx0 * CS), fmaxf(ms1, mx1 * CS), ms0, ms1, l0, l1, o);
    exp_pack(s, p, ms0, ms1, l0, l1);
    if (!own) mbar_wait(bar_full + s2 * 8, p2);
    PP_WAIT();
    wg_fence();
    wgmma_n256_rs_tb<HI128>(o, p[0], p[1], p[2], p[3], vA, 1);
    wgmma_n256_rs_tb<HI128>(o, p[4], p[5], p[6], p[7], vA + 128, 1);
    if (!own) mbar_wait(bar_full + s3 * 8, p3);
    wg_fence();
    wgmma_n256_rs_tb<HI128>(o, p[8], p[9], p[10], p[11], vB, 1);
    wgmma_n256_rs_tb<HI128>(o, p[12], p[13], p[14], p[15], vB + 128, 1);
    wg_commit();
    if (own) { PP_PASS(); }
    if (!own) {
      mbar_wait(bar_p2 + (j & 1) * 8, (j >> 1) & 1);
      const float mn0 = lds_f32(m2row + (j & 1) * 256), mn1 = lds_f32(m2row + (j & 1) * 256 + 32);
      rescale<64>(mn0, mn1, ns0, ns1, n0, n1, o2);
      wg_fence();
      pv2_half(o2, dp2, vA + wg * 512);
      pv2_half(o2, dp2 + 4, vB + wg * 512);
      wg_commit();
      PP_PASS();
    }
    wg_wait<0>();
    fence_regs(o); fence_regs(o2);
    oldv = arrive_cnt(cnt_v + (j & 1) * 4, lane);
  }
  if (oldv == 7u) { issue_seq(P, 4 * 15 + 9, sbase, bh, h); issue_seq(P, 4 * 15 + 10, sbase, bh, h); issue_wo(P, 7, sbase, h); }
  __syncwarp();

  l0 += __shfl_xor_sync(0xffffffffu, l0, 1); l1 += __shfl_xor_sync(0xffffffffu, l1, 1);
  l0 += __shfl_xor_sync(0xffffffffu, l0, 2); l1 += __shfl_xor_sync(0xffffffffu, l1, 2);
  n0 += __shfl_xor_sync(0xffffffffu, n0, 1); n1 += __shfl_xor_sync(0xffffffffu, n1, 1);
  n0 += __shfl_xor_sync(0xffffffffu, n0, 2); n1 += __shfl_xor_sync(0xffffffffu, n1, 2);
  if ((lane & 3) == 0) { sts_f32(m2row + 512 + wg * 256, n0); sts_f32(m2row + 512 + wg * 256 + 32, n1); }
  {
    const uint32_t q2row = sbase + 65536 + wg * 16384 + r * 128;
#pragma unroll
    for (int j = 0; j < 16; j += 2) {
      const int cg = j + (lane >> 4);
      const uint32_t addr = q2row + (cg >> 3) * 8192 + (((cg & 7) ^ (r & 7)) << 4);
      stsm4(addr, pack_bf16(o2[4 * j], o2[4 * j + 1]), pack_bf16(o2[4 * j + 2], o2[4 * j + 3]),
            pack_bf16(o2[4 * j + 4], o2[4 * j + 5]), pack_bf16(o2[4 * j + 6], o2[4 * j + 7]));
    }
    fence_async_smem();
    mbar_arrive(bar_o2);
  }
  uint32_t oa[64];
#pragma unroll
  for (int i = 0; i < 32; i++) {
    oa[2 * i] = pack_bf16(o[4 * i], o[4 * i + 1]);
    oa[2 * i + 1] = pack_bf16(o[4 * i + 2], o[4 * i + 3]);
  }
  {
    const float il0 = 1.0f / l0, il1 = 1.0f / l1;
    float in0 = 0.f, in1 = 0.f;
    const uint32_t stg = sbase + wg * 32768;
    char* gdst = (char*)g_part + ((size_t)(b * 4) * 32 + h * 2 + wg) * 24576;
#pragma unroll
    for (int t = 0; t < 4; t++) {
      float acc[64], acc2[32];
      uint32_t oldw[4];
      if (t < 4) {
        const int nt = (t < 3) ? 4 : 2;
        PP_WAIT();
#pragma unroll
        for (int q = 0; q < nt; q++) {
          const uint32_t w = dlo(sbase + OFF_RING, 8192) + wo_slot(4 * t + q) * 1024;
          mbar_wait(bar_full + wo_slot(4 * t + q) * 8, wo_par(4 * t + q));
          wg_fence();
          if (t < 3) {
#pragma unroll
            for (int kk = 0; kk < 4; kk++) {
              const int k = q * 4 + kk;
              wgmma_n128_rs_tb<HI128>(acc, oa[4 * k], oa[4 * k + 1], oa[4 * k + 2], oa[4 * k + 3], w + kk * 128, k > 0);
            }
            if (t == 0 && q == 0) { mbar_wait(bar_o2, 0); wg_fence(); }
#pragma unroll
            for (int kk = 0; kk < 4; kk++) {
              const int k = q * 4 + kk;
              wgmma_n64_ss_tb<HI128, HI128>(acc2, q2a + q * 512 + kk * 2, w + wg * 512 + kk * 128, k > 0);
            }
          } else {
            float (&accs)[32] = *reinterpret_cast<float (*)[32]>(&acc[0]);
            float (&acc2s)[16] = *reinterpret_cast<float (*)[16]>(&acc2[0]);
#pragma unroll
            for (int kk = 0; kk < 8; kk++) {
              const int k = q * 8 + kk;
              wgmma_n64_rs_tb<HI128>(accs, oa[4 * k], oa[4 * k + 1], oa[4 * k + 2], oa[4 * k + 3], w + kk * 128, k > 0);
            }
#pragma unroll
            for (int kk = 0; kk < 8; kk++) {
              const int k = q * 8 + kk;
              wgmma_n32_ss_tb<HI128, HI128>(acc2s, q2a + (k >> 2) * 512 + (k & 3) * 2, w + kk * 128 + wg * 4, k > 0);
            }
          }
          wg_commit();
        }
        PP_PASS();
        if ((tid & 127) == 0 && t > 0) {
          asm volatile("cp.async.bulk.wait_group 0;" ::: "memory");
          asm volatile("red.relaxed.gpu.global.add.u32 [%0], 1;" ::"l"(&g_cnt[b * 8 + t - 1]) : "memory");
        }
        __syncwarp();
        if (t == 0) {
          in0 = 1.0f / (n0 + lds_f32(m2row + 512 + (wg ^ 1) * 256));
          in1 = 1.0f / (n1 + lds_f32(m2row + 512 + (wg ^ 1) * 256 + 32));
        }
      }
      if (t < 4) {
        if (t < 2) {
#pragma unroll
          for (int q = 0; q < 4; q++) {
            if (q == 0) wg_wait<3>(); else if (q == 1) wg_wait<2>(); else if (q == 2) wg_wait<1>(); else wg_wait<0>();
            oldw[q] = arrive_cnt(cnt_wo + (4 * t + q) * 4, lane);
            if (q > 0) {
              const int m = 4 * t + (q - 1) + 8;
              if (m < 14) { if (oldw[q - 1] == 7u) issue_wo(P, m, sbase, h); __syncwarp(); }
            }
          }
          const int m = 4 * t + 3 + 8;
          if (m < 14) { if (oldw[3] == 7u) issue_wo(P, m, sbase, h); __syncwarp(); }
        } else {
          wg_wait<0>();
        }
        fence_regs(acc); fence_regs(acc2);
        if (t > 0) bar_sync(3 + wg, 128);
        const uint32_t sa = stg + (tid & 127) * 16;
        const int nv = (t < 3) ? 8 : 4;
#pragma unroll
        for (int i = 0; i < 8; i++)
          if (i < nv)
            sts_v4(sa + i * 2048, pack_bf16(acc[8 * i] * il0, acc[8 * i + 1] * il0), pack_bf16(acc[8 * i + 2] * il1, acc[8 * i + 3] * il1),
                   pack_bf16(acc[8 * i + 4] * il0, acc[8 * i + 5] * il0), pack_bf16(acc[8 * i + 6] * il1, acc[8 * i + 7] * il1));
#pragma unroll
        for (int i = 0; i < 4; i++)
          if (i < nv / 2)
            sts_v4(sa + (nv + i) * 2048, pack_bf16(acc2[8 * i] * in0, acc2[8 * i + 1] * in0), pack_bf16(acc2[8 * i + 2] * in1, acc2[8 * i + 3] * in1),
                   pack_bf16(acc2[8 * i + 4] * in0, acc2[8 * i + 5] * in0), pack_bf16(acc2[8 * i + 6] * in1, acc2[8 * i + 7] * in1));
        fence_async_smem();
        bar_sync(3 + wg, 128);
        if ((tid & 127) == 0) {
          asm volatile("cp.async.bulk.global.shared::cta.bulk_group [%0], [%1], %2;" ::"l"(gdst + (size_t)t * (32 * 24576)), "r"(stg), "r"(t < 3 ? 24576 : 12288) : "memory");
          asm volatile("cp.async.bulk.commit_group;" ::: "memory");
          if (t == 3) {
            asm volatile("cp.async.bulk.wait_group 0;" ::: "memory");
            asm volatile("red.relaxed.gpu.global.add.u32 [%0], 1;" ::"l"(&g_cnt[b * 8 + 3]) : "memory");
          }
        }
        __syncwarp();
      }
    }
  }
  if (tid < 192) {
    const unsigned int epoch1 = lds_u32(sbase + OFF_BAR + 320) + 1u;
    const unsigned int target = epoch1 * 32u;
    const char* base = (const char*)g_part + (size_t)(b * 4) * 32 * 24576;
    const int wA = tid / 96, sA = h * 96 + tid % 96, viA = sA >> 7, thA = sA & 127;
    const int wB = tid / 48, sB = h * 48 + tid % 48, viB = sB >> 7, thB = sB & 127;
    const char* srcA = base + wA * 24576 + sA * 16;
    const char* srcB = base + (size_t)3 * (32 * 24576) + wB * 24576 + sB * 16;
    __nv_bfloat16* dstA = out + ((size_t)b * SQ + (viA < 8 ? 64 * wA : 128) + (thA >> 5) * 16 + ((thA & 31) >> 2)) * DM
                          + (viA < 8 ? viA * 16 : 64 * wA + (viA - 8) * 16) + (thA & 3) * 2;
    __nv_bfloat16* dstB = out + ((size_t)b * SQ + (viB < 4 ? 64 * wB : 128) + (thB >> 5) * 16 + ((thB & 31) >> 2)) * DM
                          + 384 + (viB < 4 ? viB * 16 : 32 * wB + (viB - 4) * 16) + (thB & 3) * 2;
#pragma unroll
    for (int stage = 0; stage < 2; stage++) {
      if (lane < 2) {
        unsigned int f; int guard = 0;
        do {
          asm volatile("ld.acquire.gpu.global.u32 %0, [%1];" : "=r"(f) : "l"(&g_cnt[b * 8 + stage * 2 + lane]) : "memory");
        } while ((int)(f - target) < 0 && ++guard < (1 << 22));
      }
      __syncwarp();
      uint4 v[2][16];
#pragma unroll
      for (int hh = 0; hh < 16; hh++) v[0][hh] = __ldcg((const uint4*)(srcA + (size_t)(2 * stage) * (32 * 24576) + hh * (2 * 24576)));
      if (stage == 0) {
#pragma unroll
        for (int hh = 0; hh < 16; hh++) v[1][hh] = __ldcg((const uint4*)(srcA + (size_t)(32 * 24576) + hh * (2 * 24576)));
      } else if (tid < 96) {
#pragma unroll
        for (int hh = 0; hh < 16; hh++) v[1][hh] = __ldcg((const uint4*)(srcB + hh * (2 * 24576)));
      }
#pragma unroll
      for (int q = 0; q < 2; q++) {
        if (stage == 1 && q == 1 && tid >= 96) break;
        float a[8];
#pragma unroll
        for (int i = 0; i < 8; i++) a[i] = 0.f;
#pragma unroll
        for (int hh = 0; hh < 16; hh++) {
          const uint32_t w4[4] = {v[q][hh].x, v[q][hh].y, v[q][hh].z, v[q][hh].w};
#pragma unroll
          for (int i = 0; i < 4; i++) { a[2 * i] += bf_lo(w4[i]); a[2 * i + 1] += bf_hi(w4[i]); }
        }
        __nv_bfloat16* dst = (stage == 1 && q == 1) ? dstB : dstA + (2 * stage + q) * 128;
        *(uint32_t*)(dst) = pack_bf16(a[0], a[1]);
        *(uint32_t*)(dst + 8 * DM) = pack_bf16(a[2], a[3]);
        *(uint32_t*)(dst + 8) = pack_bf16(a[4], a[5]);
        *(uint32_t*)(dst + 8 * DM + 8) = pack_bf16(a[6], a[7]);
      }
    }
    if (tid == 0 && h == 0) g_cnt[b * 8 + 4] = epoch1;
  }
}

typedef CUresult (*EncFn)(CUtensorMap*, CUtensorMapDataType, cuuint32_t, void*, const cuuint64_t*, const cuuint64_t*,
                          const cuuint32_t*, const cuuint32_t*, CUtensorMapInterleave, CUtensorMapSwizzle,
                          CUtensorMapL2promotion, CUtensorMapFloatOOBfill);

}

extern "C" void kernel_launch(void* const* d_in, const int* in_sizes, int n_in, void* d_out, int out_size) {
  static EncFn enc = nullptr;
  static Params P;
  static const void* cached[5] = {nullptr, nullptr, nullptr, nullptr, nullptr};
  if (!enc) {
    cudaDriverEntryPointQueryResult qr;
    cudaGetDriverEntryPoint("cuTensorMapEncodeTiled", (void**)&enc, cudaEnableDefault, &qr);
    cudaFuncSetAttribute(mha_fused_kernel, cudaFuncAttributeMaxDynamicSharedMemorySize, SMEM_TOTAL);
  }
  bool same = true;
  for (int i = 0; i < 5; i++) same = same && (cached[i] == d_in[i]);
  if (!same) {
    const cuuint32_t es[3] = {1, 1, 1};
    {
      cuuint64_t dims[2] = {DM, B_ * SQ}; cuuint64_t str[1] = {DM * 2}; cuuint32_t box[2] = {32, SQ};
      enc(&P.x, CU_TENSOR_MAP_DATA_TYPE_BFLOAT16, 2, d_in[0], dims, str, box, es, CU_TENSOR_MAP_INTERLEAVE_NONE,
          CU_TENSOR_MAP_SWIZZLE_64B, CU_TENSOR_MAP_L2_PROMOTION_L2_128B, CU_TENSOR_MAP_FLOAT_OOB_FILL_NONE);
    }
    for (int w = 0; w < 2; w++) {
      cuuint64_t dims[3] = {64, (cuuint64_t)B_ * H_ * SK, 4}; cuuint64_t str[2] = {DH * 2, 128};
      cuuint32_t boxk[3] = {64, 64, 2}, boxv[3] = {64, 32, 4};
      enc(w ? &P.v : &P.k, CU_TENSOR_MAP_DATA_TYPE_BFLOAT16, 3, d_in[1 + w], dims, str, w ? boxv : boxk, es, CU_TENSOR_MAP_INTERLEAVE_NONE,
          CU_TENSOR_MAP_SWIZZLE_128B, CU_TENSOR_MAP_L2_PROMOTION_L2_256B, CU_TENSOR_MAP_FLOAT_OOB_FILL_NONE);
    }
    {
      cuuint64_t dims[3] = {64, DM, 64}; cuuint64_t str[2] = {H_ * DH * 2, 128}; cuuint32_t box[3] = {64, 32, 4};
      enc(&P.wq, CU_TENSOR_MAP_DATA_TYPE_BFLOAT16, 3, d_in[3], dims, str, box, es, CU_TENSOR_MAP_INTERLEAVE_NONE,
          CU_TENSOR_MAP_SWIZZLE_128B, CU_TENSOR_MAP_L2_PROMOTION_L2_256B, CU_TENSOR_MAP_FLOAT_OOB_FILL_NONE);
    }
    {
      cuuint64_t dims[2] = {DM, H_ * DH}; cuuint64_t str[1] = {DM * 2}; cuuint32_t box[2] = {64, 128};
      enc(&P.wo, CU_TENSOR_MAP_DATA_TYPE_BFLOAT16, 2, d_in[4], dims, str, box, es, CU_TENSOR_MAP_INTERLEAVE_NONE,
          CU_TENSOR_MAP_SWIZZLE_128B, CU_TENSOR_MAP_L2_PROMOTION_L2_128B, CU_TENSOR_MAP_FLOAT_OOB_FILL_NONE);
    }
    {
      cuuint64_t dims[3] = {64, H_ * DH, 7}; cuuint64_t str[2] = {DM * 2, 128}; cuuint32_t box[3] = {64, 64, 2};
      enc(&P.wo3, CU_TENSOR_MAP_DATA_TYPE_BFLOAT16, 3, d_in[4], dims, str, box, es, CU_TENSOR_MAP_INTERLEAVE_NONE,
          CU_TENSOR_MAP_SWIZZLE_128B, CU_TENSOR_MAP_L2_PROMOTION_L2_256B, CU_TENSOR_MAP_FLOAT_OOB_FILL_NONE);
    }
    for (int i = 0; i < 5; i++) cached[i] = d_in[i];
  }
  mha_fused_kernel<<<B_ * H_, NTHREADS, SMEM_TOTAL>>>(P, (__nv_bfloat16*)d_out);
}
```
